```python
import torch

def _softmax(x, axis=-1):
    return torch.softmax(x, dim=axis)
def _gelu(x):
    return torch.nn.functional.gelu(x, approximate="tanh")
def _silu(x):
    return torch.nn.functional.silu(x)
def _sigmoid(x):
    return torch.sigmoid(x)
def _layernorm(x, axis=-1, eps=1e-5):
    m = x.mean(dim=axis, keepdim=True)
    v = x.var(dim=axis, keepdim=True, unbiased=False)
    return (x - m) / torch.sqrt(v + eps)
def _scatter_add(tgt, idx, src, axis=0):
    return tgt.clone().index_add_(axis, idx, src)
def _segment_sum(src, seg, n):
    out = torch.zeros((n,) + src.shape[1:], dtype=src.dtype)
    return out.index_add_(0, seg, src)
def _pad(x, pw):
    flat = tuple(v for pair in reversed(pw) for v in pair)
    return torch.nn.functional.pad(x, flat)

kernel_name = 'recurrent_scan__sliding_block_cached__dense_activation_silu__decode'

def setup_inputs():

    _w = (lambda a: (lambda t: t.to(torch.bfloat16) if t.is_floating_point() else t)(torch.as_tensor(a)))
    def _A_setup():
        B, Sq, D = 4, 1, 576
        Hq, Hkv, Sk, Dh = 32, 16, 4096, 128
        assert Hq % Hkv == 0, (Hq, Hkv)
        return {
            "x": _w((lambda *s: torch.randn(*s, dtype=torch.bfloat16) * 0.1)(B, Sq, D)),
            "k_cache": _w((lambda *s: torch.randn(*s, dtype=torch.bfloat16) * 0.8)(B, Hkv, Sk, Dh)),
            "v_cache": _w((lambda *s: torch.randn(*s, dtype=torch.bfloat16) * 3.2)(B, Hkv, Sk, Dh)),
            "wq": _w((lambda *s: torch.randn(*s, dtype=torch.bfloat16) * 0.8)(D, Hq * Dh) * (D ** -0.5)),
            "wo": _w((lambda *s: torch.randn(*s, dtype=torch.bfloat16) * 3.2)(Hq * Dh, D) * ((Hq * Dh) ** -0.5)),
        }
    _A_in = _A_setup()

    def _B_setup():
        B, S, D, F = 4, 1, 576, 4608
        return {
            "x": _w((lambda *s: torch.randn(*s, dtype=torch.bfloat16) * 0.1)(B, S, D)),
            "w1": _w((lambda *s: torch.randn(*s, dtype=torch.bfloat16) * 3.2)(D, F) * (D ** -0.5)),
            "w2": _w((lambda *s: torch.randn(*s, dtype=torch.bfloat16) * 3.2)(F, D) * (F ** -0.5)),
        }
    _B_in = _B_setup()

    return {
        "A_x": _A_in["x"],
        "A_k_cache": _A_in["k_cache"],
        "A_v_cache": _A_in["v_cache"],
        "A_wq": _A_in["wq"],
        "A_wo": _A_in["wo"],
        "B_x": _B_in["x"],
        "B_w1": _B_in["w1"],
        "B_w2": _B_in["w2"],
    }

def reference(A_x, A_k_cache, A_v_cache, A_wq, A_wo, B_x, B_w1, B_w2):
    def _A_ref(x, k_cache, v_cache, wq, wo):
        B, Sq, D = x.shape
        Hq, Dh = 32, 128
        Hkv, Sk = k_cache.shape[1], k_cache.shape[2]
        W = min(4096, max(256, Sk // 4))
        rep = Hq // Hkv
        q = (lambda x, *d: x.permute(*d))((x @ wq).reshape(B, Sq, Hq, Dh), 0, 2, 1, 3)
        k = (lambda x, n, axis: torch.repeat_interleave(x, n, dim=axis))(k_cache[:, :, Sk - W:, :], rep, axis=1)
        v = (lambda x, n, axis: torch.repeat_interleave(x, n, dim=axis))(v_cache[:, :, Sk - W:, :], rep, axis=1)
        scores = torch.einsum("bhqd,bhkd->bhqk", q, k) * (Dh ** -0.5)
        p = _softmax(scores, axis=-1)
        o = torch.einsum("bhqk,bhkd->bhqd", p, v)
        return (lambda x, *d: x.permute(*d))(o, 0, 2, 1, 3).reshape(B, Sq, Hq * Dh) @ wo

    def _B_ref(x, w1, w2):
        h = torch.einsum("bsd,df->bsf", x, w1)
        h = _silu(h)
        out = torch.einsum("bsf,fd->bsd", h, w2)
        return out

    x = A_x
    xn = _layernorm(x, axis=-1)
    s = _A_ref(xn, A_k_cache, A_v_cache, A_wq, A_wo)
    g = _silu(_B_ref(xn, B_w1, B_w2))
    return x + s * g
```

```cpp
#include <cuda_runtime.h>
#include <cuda_bf16.h>
#include <cuda.h>
#include <stdint.h>

namespace {

constexpr int kB = 4, kD = 576, kHkv = 16, kSk = 4096, kDh = 128, kWin = 1024, kF = 4608;
constexpr int kNQ = 4096;
constexpr int kGroups = 16, kRanks = 8, kCTAs = 128;
constexpr int kRows1 = 72;
constexpr int kQCols = 256, kHCols = 288;
constexpr int kWoRows = 32, kW2Rows = 36;
constexpr int kChunkKeys = 64;
constexpr int kFinalCons = 96;

constexpr int kSlotBytes = 16384;
constexpr int OFF_KV = 0;
constexpr int STR_WQ = 528, STR_W1 = 592, STR_W = 1168;
constexpr int OFF_A = 8 * kSlotBytes;
constexpr int SZ_A = kRows1 * STR_WQ;
constexpr int OFF_B = OFF_A + SZ_A;
constexpr int W2_SHIFT = 576;
constexpr int SZ_B = W2_SHIFT + 40 * STR_W;
constexpr int OFF_XN = OFF_B + SZ_B;
constexpr int OFF_Q = OFF_XN + 640;
constexpr int OFF_H = OFF_Q + 544;
constexpr int OFF_O = OFF_H + 384;
constexpr int OFF_RED = OFF_O + 320;
constexpr int OFF_BAR = OFF_RED + 3072;
constexpr int SMEM_USED = OFF_BAR + 128;
constexpr int SMEM_BYTES = SMEM_USED + 1024;

static_assert(OFF_RED % 16 == 0, "align");
static_assert(OFF_BAR % 8 == 0, "align");
static_assert(SMEM_BYTES <= 232448, "smem");

__device__ uint32_t g_qpart[kGroups * kRanks * kB * kQCols];
__device__ uint32_t g_hpart[kGroups * kRanks * kB * kHCols];
__device__ uint32_t g_opart[kGroups * kB * 2 * 16 * 132];
__device__ __align__(16) uint32_t g_fpart[kFinalCons * kCTAs * 48];
__device__ uint32_t g_epoch;

constexpr int kSpinLimit = 1 << 22;

__device__ __forceinline__ uint32_t smem_u32(const void* p) {
    return (uint32_t)__cvta_generic_to_shared(p);
}
__device__ __forceinline__ void mbar_init(uint32_t bar, uint32_t count) {
    asm volatile("mbarrier.init.shared::cta.b64 [%0], %1;" ::"r"(bar), "r"(count) : "memory");
}
__device__ __forceinline__ void mbar_expect_tx(uint32_t bar, uint32_t bytes) {
    asm volatile("mbarrier.arrive.expect_tx.shared::cta.b64 _, [%0], %1;" ::"r"(bar), "r"(bytes) : "memory");
}
__device__ __forceinline__ void mbar_arrive(uint32_t bar) {
    asm volatile("mbarrier.arrive.shared::cta.b64 _, [%0];" ::"r"(bar) : "memory");
}
__device__ __forceinline__ bool mbar_try_wait(uint32_t bar, uint32_t parity) {
    uint32_t ok;
    asm volatile(
        "{\n .reg .pred p;\n mbarrier.try_wait.parity.shared::cta.b64 p, [%1], %2;\n selp.u32 %0, 1, 0, p;\n}"
        : "=r"(ok)
        : "r"(bar), "r"(parity)
        : "memory");
    return ok != 0;
}
__device__ __forceinline__ void mbar_wait(uint32_t bar, uint32_t parity) {
    for (int i = 0; i < kSpinLimit; i++) {
        if (mbar_try_wait(bar, parity)) break;
    }
}
__device__ __forceinline__ void bulk_g2s(uint32_t dst, const void* src, uint32_t bytes, uint32_t bar) {
    asm volatile(
        "cp.async.bulk.shared::cluster.global.mbarrier::complete_tx::bytes [%0], [%1], %2, [%3];" ::"r"(dst),
        "l"(src), "r"(bytes), "r"(bar)
        : "memory");
}
__device__ __forceinline__ void tma_2d(uint32_t dst, const CUtensorMap* map, int c0, int c1, uint32_t bar) {
    asm volatile(
        "cp.async.bulk.tensor.2d.shared::cluster.global.mbarrier::complete_tx::bytes [%0], [%1, {%3, %4}], [%2];" ::"r"(dst),
        "l"(map), "r"(bar), "r"(c0), "r"(c1)
        : "memory");
}
__device__ __forceinline__ void ldsm_x4(uint32_t addr, uint32_t& r0, uint32_t& r1, uint32_t& r2, uint32_t& r3) {
    asm volatile("ldmatrix.sync.aligned.m8n8.x4.shared.b16 {%0,%1,%2,%3}, [%4];"
                 : "=r"(r0), "=r"(r1), "=r"(r2), "=r"(r3)
                 : "r"(addr)
                 : "memory");
}
__device__ __forceinline__ void ldsm_x4_t(uint32_t addr, uint32_t& r0, uint32_t& r1, uint32_t& r2, uint32_t& r3) {
    asm volatile("ldmatrix.sync.aligned.m8n8.x4.trans.shared.b16 {%0,%1,%2,%3}, [%4];"
                 : "=r"(r0), "=r"(r1), "=r"(r2), "=r"(r3)
                 : "r"(addr)
                 : "memory");
}
__device__ __forceinline__ void ldsm_x2_t(uint32_t addr, uint32_t& r0, uint32_t& r1) {
    asm volatile("ldmatrix.sync.aligned.m8n8.x2.trans.shared.b16 {%0,%1}, [%2];"
                 : "=r"(r0), "=r"(r1)
                 : "r"(addr)
                 : "memory");
}
__device__ __forceinline__ void mma16816(float (&c)[4], uint32_t a0, uint32_t a1, uint32_t a2, uint32_t a3,
                                         uint32_t b0, uint32_t b1) {
    asm volatile(
        "mma.sync.aligned.m16n8k16.row.col.f32.bf16.bf16.f32 {%0,%1,%2,%3}, {%4,%5,%6,%7}, {%8,%9}, {%0,%1,%2,%3};"
        : "+f"(c[0]), "+f"(c[1]), "+f"(c[2]), "+f"(c[3])
        : "r"(a0), "r"(a1), "r"(a2), "r"(a3), "r"(b0), "r"(b1));
}
__device__ __forceinline__ void mma1688(float (&c)[4], uint32_t a0, uint32_t a1, uint32_t b0) {
    asm volatile("mma.sync.aligned.m16n8k8.row.col.f32.bf16.bf16.f32 {%0,%1,%2,%3}, {%4,%5}, {%6}, {%0,%1,%2,%3};"
                 : "+f"(c[0]), "+f"(c[1]), "+f"(c[2]), "+f"(c[3])
                 : "r"(a0), "r"(a1), "r"(b0));
}
__device__ __forceinline__ void bar_cons() { asm volatile("bar.sync 1, 256;" ::: "memory"); }

__device__ __forceinline__ float bfr(float x) { return __bfloat162float(__float2bfloat16_rn(x)); }
__device__ __forceinline__ uint32_t pack_bf16(float lo, float hi) {
    __nv_bfloat162 v = __floats2bfloat162_rn(lo, hi);
    return *reinterpret_cast<uint32_t*>(&v);
}
__device__ __forceinline__ uint32_t tagw(float v, uint32_t flag) { return (__float_as_uint(v) & ~1u) | flag; }
__device__ __forceinline__ void st_word(uint32_t* p, uint32_t v) {
    asm volatile("st.relaxed.gpu.global.u32 [%0], %1;" ::"l"(p), "r"(v) : "memory");
}
__device__ __forceinline__ void st_word2(uint32_t* p, uint32_t v0, uint32_t v1) {
    asm volatile("st.relaxed.gpu.global.v2.u32 [%0], {%1,%2};" ::"l"(p), "r"(v0), "r"(v1) : "memory");
}
__device__ __forceinline__ uint32_t ld_word(const uint32_t* p) {
    uint32_t v;
    asm volatile("ld.relaxed.gpu.global.u32 %0, [%1];" : "=r"(v) : "l"(p) : "memory");
    return v;
}
__device__ __forceinline__ uint4 ld_word4(const uint32_t* p) {
    uint4 v;
    asm volatile("ld.relaxed.gpu.global.v4.u32 {%0,%1,%2,%3}, [%4];"
                 : "=r"(v.x), "=r"(v.y), "=r"(v.z), "=r"(v.w)
                 : "l"(p)
                 : "memory");
    return v;
}
__device__ __forceinline__ float silu_f(float x) { return x / (1.0f + __expf(-x)); }

__global__ void __launch_bounds__(288, 1)
fused_decode_kernel(const __grid_constant__ CUtensorMap kmap, const __grid_constant__ CUtensorMap vmap,
                    const __nv_bfloat16* __restrict__ x, const __nv_bfloat16* __restrict__ wq,
                    const __nv_bfloat16* __restrict__ wo, const __nv_bfloat16* __restrict__ w1,
                    const __nv_bfloat16* __restrict__ w2, __nv_bfloat16* __restrict__ out) {
    extern __shared__ uint8_t smem_raw[];
    const uint32_t raw_u32 = smem_u32(smem_raw);
    const uint32_t sbase = (raw_u32 + 1023u) & ~1023u;
    uint8_t* sgen = smem_raw + (sbase - raw_u32);

    const int tid = threadIdx.x, warp = tid >> 5, lane = tid & 31;
    const int cta = blockIdx.x;
    const int g = cta >> 3, r = cta & 7;
    const int b = r >> 1, half = r & 1;

    const uint32_t bar_full = sbase + OFF_BAR;
    const uint32_t bar_wA = sbase + OFF_BAR + 64;
    const uint32_t bar_wB = sbase + OFF_BAR + 72;
    const uint32_t bar_vdone = sbase + OFF_BAR + 80;

    if (tid == 0) {
        for (int i = 0; i < 8; i++) mbar_init(bar_full + 8 * i, 1);
        mbar_init(bar_wA, 1);
        mbar_init(bar_wB, 1);
        mbar_init(bar_vdone, 8);
        asm volatile("fence.mbarrier_init.release.cluster;" ::: "memory");
        asm volatile("fence.proxy.async.shared::cta;" ::: "memory");
    }
    __syncthreads();

    const int kv_row0 = (b * kHkv + g) * kSk + (kSk - kWin) + half * 512;

    if (warp == 8) {
        if (lane == 0) {
            mbar_expect_tx(bar_wA, kRows1 * 512);
            mbar_expect_tx(bar_wB, kRows1 * 576);
        }
        __syncwarp();
        for (int i = lane; i < kRows1; i += 32)
            bulk_g2s(sbase + OFF_A + i * STR_WQ, wq + (size_t)(kRows1 * r + i) * kNQ + kQCols * g, 512, bar_wA);
        __syncwarp();
        for (int i = lane; i < kRows1; i += 32)
            bulk_g2s(sbase + OFF_B + i * STR_W1, w1 + (size_t)(kRows1 * r + i) * kF + kHCols * g, 576, bar_wB);
        __syncwarp();
        if (lane < 8) {
            const uint32_t bar = bar_full + 8 * lane;
            mbar_expect_tx(bar, kSlotBytes);
            tma_2d(sbase + OFF_KV + lane * kSlotBytes, &kmap, 0, kv_row0 + kChunkKeys * lane, bar);
            tma_2d(sbase + OFF_KV + lane * kSlotBytes + 8192, &kmap, 64, kv_row0 + kChunkKeys * lane, bar);
        }
        __syncwarp();
        mbar_wait(bar_vdone, 0);
        if (lane == 0) {
            mbar_expect_tx(bar_wB, kW2Rows * 1152);
            mbar_expect_tx(bar_wA, kWoRows * 1152);
        }
        __syncwarp();
        for (int i = lane; i < kW2Rows; i += 32)
            bulk_g2s(sbase + OFF_B + W2_SHIFT + i * STR_W, w2 + (size_t)(kHCols * g + kW2Rows * r + i) * kD, 1152,
                     bar_wB);
        __syncwarp();
        bulk_g2s(sbase + OFF_A + lane * STR_W, wo + (size_t)(kQCols * g + kWoRows * r + lane) * kD, 1152, bar_wA);
        return;
    }

    uint32_t epoch;
    asm volatile("ld.relaxed.gpu.global.u32 %0, [%1];" : "=r"(epoch) : "l"(&g_epoch) : "memory");
    const uint32_t flag = (epoch + 1u) & 1u;

    __nv_bfloat16* xn_s = reinterpret_cast<__nv_bfloat16*>(sgen + OFF_XN);
    __nv_bfloat16* q_s = reinterpret_cast<__nv_bfloat16*>(sgen + OFF_Q);
    __nv_bfloat16* h_s = reinterpret_cast<__nv_bfloat16*>(sgen + OFF_H);
    __nv_bfloat16* o_s = reinterpret_cast<__nv_bfloat16*>(sgen + OFF_O);

    if (warp < 4) {
        const uint32_t* xr = reinterpret_cast<const uint32_t*>(x + warp * kD);
        float v[18];
        float sum = 0.f;
#pragma unroll
        for (int i = 0; i < 9; i++) {
            uint32_t w = __ldg(xr + lane + 32 * i);
            v[2 * i] = __uint_as_float(w << 16);
            v[2 * i + 1] = __uint_as_float(w & 0xffff0000u);
            sum += v[2 * i] + v[2 * i + 1];
        }
#pragma unroll
        for (int o = 16; o > 0; o >>= 1) sum += __shfl_xor_sync(0xffffffffu, sum, o);
        const float mean = sum * (1.0f / kD);
        float sq = 0.f;
#pragma unroll
        for (int i = 0; i < 18; i++) {
            float d = v[i] - mean;
            sq += d * d;
        }
#pragma unroll
        for (int o = 16; o > 0; o >>= 1) sq += __shfl_xor_sync(0xffffffffu, sq, o);
        const float m_bf = bfr(mean);
        const float v_bf = bfr(sq * (1.0f / kD));
        const float den = bfr(sqrtf(bfr(v_bf + 1e-5f)));
#pragma unroll
        for (int i = 0; i < 9; i++) {
            int e = 2 * (lane + 32 * i) - kRows1 * r;
            if (e >= 0 && e < kRows1) {
                float a0 = bfr(v[2 * i] - m_bf) / den;
                float a1 = bfr(v[2 * i + 1] - m_bf) / den;
                *reinterpret_cast<uint32_t*>(xn_s + warp * 80 + e) = pack_bf16(a0, a1);
            }
        }
    } else {
        uint4* z = reinterpret_cast<uint4*>(sgen + OFF_B + W2_SHIFT + kW2Rows * STR_W);
        for (int i = tid - 128; i < 4 * STR_W / 16; i += 128) z[i] = make_uint4(0, 0, 0, 0);
        if (tid - 128 < 96) reinterpret_cast<uint32_t*>(h_s)[tid - 128] = 0u;
    }
    bar_cons();

    const int gid = lane >> 2, tig = lane & 3;
    const int lm_i = lane & 7, lm_j = lane >> 3;

    {
        uint32_t bx[9];
#pragma unroll
        for (int ks = 0; ks < 4; ks++) {
            bx[2 * ks] = gid < 4 ? *reinterpret_cast<const uint32_t*>(xn_s + gid * 80 + 16 * ks + 2 * tig) : 0u;
            bx[2 * ks + 1] = gid < 4 ? *reinterpret_cast<const uint32_t*>(xn_s + gid * 80 + 16 * ks + 8 + 2 * tig) : 0u;
        }
        bx[8] = gid < 4 ? *reinterpret_cast<const uint32_t*>(xn_s + gid * 80 + 64 + 2 * tig) : 0u;

        mbar_wait(bar_wA, 0);
        uint32_t* qdst = g_qpart + (size_t)(g * kRanks + r) * kB * kQCols;
#pragma unroll
        for (int t = 0; t < 2; t++) {
            const int m0 = 16 * (warp + 8 * t);
            float c[4] = {0.f, 0.f, 0.f, 0.f};
            const uint32_t abase = sbase + OFF_A + (lm_i + (lm_j >> 1) * 8) * STR_WQ + (m0 + (lm_j & 1) * 8) * 2;
#pragma unroll
            for (int ks = 0; ks < 4; ks++) {
                uint32_t a0, a1, a2, a3;
                ldsm_x4_t(abase + ks * 16 * STR_WQ, a0, a1, a2, a3);
                mma16816(c, a0, a1, a2, a3, bx[2 * ks], bx[2 * ks + 1]);
            }
            {
                uint32_t a0, a1;
                ldsm_x2_t(sbase + OFF_A + (64 + lm_i) * STR_WQ + (m0 + (lm_j & 1) * 8) * 2, a0, a1);
                mma1688(c, a0, a1, bx[8]);
            }
            if (tig < 2) {
                const int col = m0 + gid;
                st_word(qdst + (2 * tig) * kQCols + col, tagw(c[0], flag));
                st_word(qdst + (2 * tig + 1) * kQCols + col, tagw(c[1], flag));
                st_word(qdst + (2 * tig) * kQCols + col + 8, tagw(c[2], flag));
                st_word(qdst + (2 * tig + 1) * kQCols + col + 8, tagw(c[3], flag));
            }
        }
        mbar_wait(bar_wB, 0);
        uint32_t* hdst = g_hpart + (size_t)(g * kRanks + r) * kB * kHCols;
        for (int t = warp; t < 18; t += 8) {
            const int m0 = 16 * t;
            float c[4] = {0.f, 0.f, 0.f, 0.f};
            const uint32_t abase = sbase + OFF_B + (lm_i + (lm_j >> 1) * 8) * STR_W1 + (m0 + (lm_j & 1) * 8) * 2;
#pragma unroll
            for (int ks = 0; ks < 4; ks++) {
                uint32_t a0, a1, a2, a3;
                ldsm_x4_t(abase + ks * 16 * STR_W1, a0, a1, a2, a3);
                mma16816(c, a0, a1, a2, a3, bx[2 * ks], bx[2 * ks + 1]);
            }
            {
                uint32_t a0, a1;
                ldsm_x2_t(sbase + OFF_B + (64 + lm_i) * STR_W1 + (m0 + (lm_j & 1) * 8) * 2, a0, a1);
                mma1688(c, a0, a1, bx[8]);
            }
            if (tig < 2) {
                const int col = m0 + gid;
                st_word(hdst + (2 * tig) * kHCols + col, tagw(c[0], flag));
                st_word(hdst + (2 * tig + 1) * kHCols + col, tagw(c[1], flag));
                st_word(hdst + (2 * tig) * kHCols + col + 8, tagw(c[2], flag));
                st_word(hdst + (2 * tig + 1) * kHCols + col + 8, tagw(c[3], flag));
            }
        }
    }

    {
        const uint32_t* src = g_qpart + (size_t)(g * kRanks) * kB * kQCols + b * kQCols + tid;
        uint32_t w[8];
        for (int it = 0; it < kSpinLimit; it++) {
            uint32_t ok = 1;
#pragma unroll
            for (int p = 0; p < 8; p++) {
                w[p] = ld_word(src + p * kB * kQCols);
                ok &= ((w[p] ^ flag) & 1u) ^ 1u;
            }
            if (ok) break;
        }
        float s = 0.f;
#pragma unroll
        for (int p = 0; p < 8; p++) s += __uint_as_float(w[p]);
        q_s[(tid >> 7) * 136 + (tid & 127)] = __float2bfloat16_rn(s);
    }
    bar_cons();

    {
        uint32_t qa[16];
#pragma unroll
        for (int j = 0; j < 8; j++) {
            qa[2 * j] = gid < 2 ? *reinterpret_cast<const uint32_t*>(q_s + gid * 136 + 16 * j + 2 * tig) : 0u;
            qa[2 * j + 1] = gid < 2 ? *reinterpret_cast<const uint32_t*>(q_s + gid * 136 + 16 * j + 8 + 2 * tig) : 0u;
        }
        const uint32_t slot = sbase + OFF_KV + warp * kSlotBytes;
        const uint32_t bar = bar_full + 8 * warp;
        mbar_wait(bar, 0);
        float sc[8][4];
#pragma unroll
        for (int nt = 0; nt < 8; nt++) {
            sc[nt][0] = sc[nt][1] = sc[nt][2] = sc[nt][3] = 0.f;
#pragma unroll
            for (int kk = 0; kk < 4; kk++) {
                const int cg = 4 * kk + lm_j;
                const uint32_t addr =
                    slot + (cg >> 3) * 8192 + (8 * nt + lm_i) * 128 + (((cg & 7) ^ lm_i) << 4);
                uint32_t b0, b1, b2, b3;
                ldsm_x4(addr, b0, b1, b2, b3);
                mma16816(sc[nt], qa[4 * kk], 0u, qa[4 * kk + 1], 0u, b0, b1);
                mma16816(sc[nt], qa[4 * kk + 2], 0u, qa[4 * kk + 3], 0u, b2, b3);
            }
        }
        float mx = -INFINITY;
        const float scale = 0.08838834764831845f;
#pragma unroll
        for (int nt = 0; nt < 8; nt++) {
            sc[nt][0] = bfr(bfr(sc[nt][0]) * scale);
            sc[nt][1] = bfr(bfr(sc[nt][1]) * scale);
            mx = fmaxf(mx, fmaxf(sc[nt][0], sc[nt][1]));
        }
        __syncwarp();
        if (lane == 0) {
            mbar_expect_tx(bar, kSlotBytes);
            tma_2d(slot, &vmap, 0, kv_row0 + kChunkKeys * warp, bar);
            tma_2d(slot + 8192, &vmap, 64, kv_row0 + kChunkKeys * warp, bar);
            mbar_arrive(bar_vdone);
        }
        mx = fmaxf(mx, __shfl_xor_sync(0xffffffffu, mx, 1));
        mx = fmaxf(mx, __shfl_xor_sync(0xffffffffu, mx, 2));
        const float l2e = 1.4426950408889634f;
        float lsum = 0.f;
        uint32_t pb[8];
#pragma unroll
        for (int nt = 0; nt < 8; nt++) {
            float p0 = exp2f((sc[nt][0] - mx) * l2e);
            float p1 = exp2f((sc[nt][1] - mx) * l2e);
            lsum += p0 + p1;
            pb[nt] = pack_bf16(p0, p1);
        }
        lsum += __shfl_xor_sync(0xffffffffu, lsum, 1);
        lsum += __shfl_xor_sync(0xffffffffu, lsum, 2);

        mbar_wait(bar, 1);
        uint32_t* odst = g_opart + (size_t)(((g * kB + b) * 2) * 16 + half * 8 + warp) * 132;
#pragma unroll
        for (int mt = 0; mt < 8; mt++) {
            float oc[4] = {0.f, 0.f, 0.f, 0.f};
            const int cg = 2 * mt + (lm_j & 1);
#pragma unroll
            for (int ks = 0; ks < 4; ks++) {
                const int key = 16 * ks + (lm_j >> 1) * 8 + lm_i;
                const uint32_t addr = slot + (cg >> 3) * 8192 + key * 128 + (((cg & 7) ^ lm_i) << 4);
                uint32_t a0, a1, a2, a3;
                ldsm_x4_t(addr, a0, a1, a2, a3);
                mma16816(oc, a0, a1, a2, a3, pb[2 * ks], pb[2 * ks + 1]);
            }
            if (tig == 0) {
                const int d = 16 * mt + gid;
                st_word(odst + d, tagw(oc[0], flag));
                st_word(odst + 16 * 132 + d, tagw(oc[1], flag));
                st_word(odst + d + 8, tagw(oc[2], flag));
                st_word(odst + 16 * 132 + d + 8, tagw(oc[3], flag));
            }
        }
        if (lane == 0 || lane == 4) {
            uint32_t* dst = odst + (lane >> 2) * 16 * 132 + 128;
            st_word2(dst, tagw(mx, flag), tagw(lsum, flag));
        }
    }

    if (tid < 128) {
        const int bb = tid >> 5, d = tid & 31;
        const int head = r >> 2, dim = 32 * (r & 3) + d;
        const uint32_t* src = g_opart + (size_t)(((g * kB + bb) * 2 + head) * 16) * 132;
        uint32_t wo_[16], wm[16], wl[16];
        for (int it = 0; it < kSpinLimit; it++) {
            uint32_t ok = 1;
#pragma unroll
            for (int p = 0; p < 16; p++) {
                wo_[p] = ld_word(src + p * 132 + dim);
                wm[p] = ld_word(src + p * 132 + 128);
                wl[p] = ld_word(src + p * 132 + 129);
                ok &= (((wo_[p] ^ flag) | (wm[p] ^ flag) | (wl[p] ^ flag)) & 1u) ^ 1u;
            }
            if (ok) break;
        }
        float M = -INFINITY;
#pragma unroll
        for (int p = 0; p < 16; p++) M = fmaxf(M, __uint_as_float(wm[p]));
        float L = 0.f, O = 0.f;
#pragma unroll
        for (int p = 0; p < 16; p++) {
            float wgt = exp2f((__uint_as_float(wm[p]) - M) * 1.4426950408889634f);
            L += wgt * __uint_as_float(wl[p]);
            O += wgt * __uint_as_float(wo_[p]);
        }
        o_s[bb * 40 + d] = __float2bfloat16_rn(O / L);
    } else {
        for (int idx = tid - 128; idx < kB * kW2Rows; idx += 128) {
            const int bb = idx / kW2Rows, j = idx - bb * kW2Rows;
            const uint32_t* src = g_hpart + (size_t)(g * kRanks) * kB * kHCols + bb * kHCols + kW2Rows * r + j;
            uint32_t w[8];
            for (int it = 0; it < kSpinLimit; it++) {
                uint32_t ok = 1;
#pragma unroll
                for (int p = 0; p < 8; p++) {
                    w[p] = ld_word(src + p * kB * kHCols);
                    ok &= ((w[p] ^ flag) & 1u) ^ 1u;
                }
                if (ok) break;
            }
            float s = 0.f;
#pragma unroll
            for (int p = 0; p < 8; p++) s += __uint_as_float(w[p]);
            h_s[bb * 48 + j] = __float2bfloat16_rn(silu_f(bfr(s)));
        }
    }
    bar_cons();

    {
        uint32_t bh[5], bo[4];
#pragma unroll
        for (int ks = 0; ks < 2; ks++) {
            bh[2 * ks] = gid < 4 ? *reinterpret_cast<const uint32_t*>(h_s + gid * 48 + 16 * ks + 2 * tig) : 0u;
            bh[2 * ks + 1] = gid < 4 ? *reinterpret_cast<const uint32_t*>(h_s + gid * 48 + 16 * ks + 8 + 2 * tig) : 0u;
            bo[2 * ks] = gid < 4 ? *reinterpret_cast<const uint32_t*>(o_s + gid * 40 + 16 * ks + 2 * tig) : 0u;
            bo[2 * ks + 1] = gid < 4 ? *reinterpret_cast<const uint32_t*>(o_s + gid * 40 + 16 * ks + 8 + 2 * tig) : 0u;
        }
        bh[4] = gid < 4 ? *reinterpret_cast<const uint32_t*>(h_s + gid * 48 + 32 + 2 * tig) : 0u;

        mbar_wait(bar_wB, 1);
        for (int t = warp; t < 36; t += 8) {
            const int m0 = 16 * t;
            float c[4] = {0.f, 0.f, 0.f, 0.f};
            const uint32_t abase =
                sbase + OFF_B + W2_SHIFT + (lm_i + (lm_j >> 1) * 8) * STR_W + (m0 + (lm_j & 1) * 8) * 2;
#pragma unroll
            for (int ks = 0; ks < 2; ks++) {
                uint32_t a0, a1, a2, a3;
                ldsm_x4_t(abase + ks * 16 * STR_W, a0, a1, a2, a3);
                mma16816(c, a0, a1, a2, a3, bh[2 * ks], bh[2 * ks + 1]);
            }
            {
                uint32_t a0, a1;
                ldsm_x2_t(sbase + OFF_B + W2_SHIFT + (32 + lm_i) * STR_W + (m0 + (lm_j & 1) * 8) * 2, a0, a1);
                mma1688(c, a0, a1, bh[4]);
            }
            if (tig < 2) {
                const int col0 = m0 + gid, col1 = col0 + 8;
                const int j0 = col0 / 6, j1 = col1 / 6;
                st_word2(g_fpart + (size_t)(j0 * kCTAs + cta) * 48 + 24 + (col0 - 6 * j0) * 4 + 2 * tig,
                         tagw(c[0], flag), tagw(c[1], flag));
                st_word2(g_fpart + (size_t)(j1 * kCTAs + cta) * 48 + 24 + (col1 - 6 * j1) * 4 + 2 * tig,
                         tagw(c[2], flag), tagw(c[3], flag));
            }
        }
        mbar_wait(bar_wA, 1);
        for (int t = warp; t < 36; t += 8) {
            const int m0 = 16 * t;
            float c[4] = {0.f, 0.f, 0.f, 0.f};
            const uint32_t abase = sbase + OFF_A + (lm_i + (lm_j >> 1) * 8) * STR_W + (m0 + (lm_j & 1) * 8) * 2;
#pragma unroll
            for (int ks = 0; ks < 2; ks++) {
                uint32_t a0, a1, a2, a3;
                ldsm_x4_t(abase + ks * 16 * STR_W, a0, a1, a2, a3);
                mma16816(c, a0, a1, a2, a3, bo[2 * ks], bo[2 * ks + 1]);
            }
            if (tig < 2) {
                const int col0 = m0 + gid, col1 = col0 + 8;
                const int j0 = col0 / 6, j1 = col1 / 6;
                st_word2(g_fpart + (size_t)(j0 * kCTAs + cta) * 48 + (col0 - 6 * j0) * 4 + 2 * tig,
                         tagw(c[0], flag), tagw(c[1], flag));
                st_word2(g_fpart + (size_t)(j1 * kCTAs + cta) * 48 + (col1 - 6 * j1) * 4 + 2 * tig,
                         tagw(c[2], flag), tagw(c[3], flag));
            }
        }
    }

    if (cta < kFinalCons) {
        float4* red = reinterpret_cast<float4*>(sgen + OFF_RED);
        if (tid < 192) {
            const int c4 = tid % 12, p0 = tid / 12;
            const uint32_t* src = g_fpart + (size_t)(cta * kCTAs + p0) * 48 + c4 * 4;
            uint4 w[8];
            for (int it = 0; it < kSpinLimit; it++) {
                uint32_t ok = 1;
#pragma unroll
                for (int i = 0; i < 8; i++) {
                    w[i] = ld_word4(src + (size_t)i * 16 * 48);
                    ok &= (((w[i].x ^ flag) | (w[i].y ^ flag) | (w[i].z ^ flag) | (w[i].w ^ flag)) & 1u) ^ 1u;
                }
                if (ok) break;
            }
            float4 s = make_float4(0.f, 0.f, 0.f, 0.f);
#pragma unroll
            for (int i = 0; i < 8; i++) {
                s.x += __uint_as_float(w[i].x);
                s.y += __uint_as_float(w[i].y);
                s.z += __uint_as_float(w[i].z);
                s.w += __uint_as_float(w[i].w);
            }
            red[p0 * 12 + c4] = s;
        }
        bar_cons();
        if (tid < 24) {
            const float* rf = reinterpret_cast<const float*>(red);
            float sv = 0.f, gv = 0.f;
#pragma unroll
            for (int p = 0; p < 16; p++) {
                sv += rf[p * 48 + tid];
                gv += rf[p * 48 + 24 + tid];
            }
            const int col = 6 * cta + (tid >> 2), bb = tid & 3;
            const float xv = __bfloat162float(x[bb * kD + col]);
            const float gg = bfr(silu_f(bfr(gv)));
            const float sg = bfr(bfr(sv) * gg);
            out[bb * kD + col] = __float2bfloat16_rn(xv + sg);
        }
        if (cta == 0 && tid == 0) {
            asm volatile("st.relaxed.gpu.global.u32 [%0], %1;" ::"l"(&g_epoch), "r"(epoch + 1u) : "memory");
        }
    }
}

typedef CUresult (*PFN_encodeTiled)(CUtensorMap*, CUtensorMapDataType, cuuint32_t, void*, const cuuint64_t*,
                                    const cuuint64_t*, const cuuint32_t*, const cuuint32_t*, CUtensorMapInterleave,
                                    CUtensorMapSwizzle, CUtensorMapL2promotion, CUtensorMapFloatOOBfill);

void make_kv_map(PFN_encodeTiled enc, CUtensorMap* map, const void* ptr) {
    cuuint64_t gdim[2] = {(cuuint64_t)kDh, (cuuint64_t)kB * kHkv * kSk};
    cuuint64_t gstr[1] = {(cuuint64_t)kDh * 2};
    cuuint32_t box[2] = {64, (cuuint32_t)kChunkKeys};
    cuuint32_t estr[2] = {1, 1};
    enc(map, CU_TENSOR_MAP_DATA_TYPE_BFLOAT16, 2, const_cast<void*>(ptr), gdim, gstr, box, estr,
        CU_TENSOR_MAP_INTERLEAVE_NONE, CU_TENSOR_MAP_SWIZZLE_128B, CU_TENSOR_MAP_L2_PROMOTION_L2_256B,
        CU_TENSOR_MAP_FLOAT_OOB_FILL_NONE);
}

}

extern "C" void kernel_launch(void* const* d_in, const int* in_sizes, int n_in, void* d_out, int out_size) {
    (void)in_sizes;
    (void)n_in;
    (void)out_size;
    static PFN_encodeTiled enc = nullptr;
    if (!enc) {
        void* fn = nullptr;
        cudaDriverEntryPointQueryResult st;
        cudaGetDriverEntryPoint("cuTensorMapEncodeTiled", &fn, cudaEnableDefault, &st);
        enc = (PFN_encodeTiled)fn;
        cudaFuncSetAttribute(fused_decode_kernel, cudaFuncAttributeMaxDynamicSharedMemorySize, SMEM_BYTES);
    }
    CUtensorMap kmap, vmap;
    make_kv_map(enc, &kmap, d_in[1]);
    make_kv_map(enc, &vmap, d_in[2]);
    fused_decode_kernel<<<kCTAs, 288, SMEM_BYTES>>>(
        kmap, vmap, (const __nv_bfloat16*)d_in[0], (const __nv_bfloat16*)d_in[3], (const __nv_bfloat16*)d_in[4],
        (const __nv_bfloat16*)d_in[6], (const __nv_bfloat16*)d_in[7], (__nv_bfloat16*)d_out);
}
```

```cpp
#include <cuda_runtime.h>
#include <cuda_bf16.h>
#include <cuda.h>
#include <stdint.h>

namespace {

constexpr int kB = 4, kD = 576, kHkv = 16, kSk = 4096, kDh = 128, kWin = 1024, kF = 4608;
constexpr int kNQ = 4096;
constexpr int kGroups = 16, kRanks = 8, kCTAs = 128;
constexpr int kRows1 = 72;
constexpr int kQCols = 256, kHCols = 288;
constexpr int kCols3 = 72;
constexpr int kChunkKeys = 64;
constexpr int kFinalCons = 72;

constexpr int kSlotBytes = 16384;
constexpr int OFF_KV = 0;
constexpr int STR_WQ = 528, STR_W1 = 592, STR_W3 = 144;
constexpr int OFF_A = 8 * kSlotBytes;
constexpr int SZ_A = kRows1 * STR_WQ;
constexpr int OFF_B = OFF_A + SZ_A;
constexpr int SZ_B = kRows1 * STR_W1;
constexpr int OFF_XN = OFF_B + SZ_B;
constexpr int OFF_Q = OFF_XN + 640;
constexpr int OFF_H = OFF_Q + 544;
constexpr int OFF_O = OFF_H + 4 * 296 * 2;
constexpr int OFF_OW = OFF_O + 4 * 264 * 2;
constexpr int OFF_ML = OFF_OW + 8 * 256 * 4;
constexpr int OFF_RED = OFF_ML + 128;
constexpr int OFF_BAR = OFF_RED + 1024;
constexpr int SMEM_USED = OFF_BAR + 288;
constexpr int SMEM_BYTES = SMEM_USED + 1024;

static_assert(OFF_A % 128 == 0 && OFF_B % 128 == 0, "align");
static_assert(OFF_OW % 16 == 0 && OFF_RED % 16 == 0, "align");
static_assert(OFF_BAR % 8 == 0, "align");
static_assert(SMEM_BYTES <= 232448, "smem");

__device__ __align__(128) uint32_t g_qpart[kGroups * kRanks * kB * kQCols];
__device__ __align__(128) uint32_t g_hpart[kGroups * kRanks * kB * kHCols];
__device__ __align__(128) uint32_t g_opart[kGroups * kB * 2 * 2 * 136];
__device__ __align__(128) uint32_t g_fpart[kFinalCons * 2 * kGroups * 32];
__device__ uint32_t g_epoch;

constexpr int kSpinLimit = 1 << 22;
#define KWINDOW 4
constexpr int kWindow = KWINDOW;

#define TS(k)

__device__ __forceinline__ uint32_t smem_u32(const void* p) {
    return (uint32_t)__cvta_generic_to_shared(p);
}
__device__ __forceinline__ void mbar_init(uint32_t bar, uint32_t count) {
    asm volatile("mbarrier.init.shared::cta.b64 [%0], %1;" ::"r"(bar), "r"(count) : "memory");
}
__device__ __forceinline__ void mbar_expect_tx(uint32_t bar, uint32_t bytes) {
    asm volatile("mbarrier.arrive.expect_tx.shared::cta.b64 _, [%0], %1;" ::"r"(bar), "r"(bytes) : "memory");
}
__device__ __forceinline__ void mbar_arrive(uint32_t bar) {
    asm volatile("mbarrier.arrive.shared::cta.b64 _, [%0];" ::"r"(bar) : "memory");
}
__device__ __forceinline__ bool mbar_try_wait(uint32_t bar, uint32_t parity) {
    uint32_t ok;
    asm volatile(
        "{\n .reg .pred p;\n mbarrier.try_wait.parity.shared::cta.b64 p, [%1], %2;\n selp.u32 %0, 1, 0, p;\n}"
        : "=r"(ok)
        : "r"(bar), "r"(parity)
        : "memory");
    return ok != 0;
}
__device__ __forceinline__ void mbar_wait(uint32_t bar, uint32_t parity) {
    for (int i = 0; i < kSpinLimit; i++) {
        if (mbar_try_wait(bar, parity)) break;
    }
}
__device__ __forceinline__ void bulk_g2s(uint32_t dst, const void* src, uint32_t bytes, uint32_t bar) {
    asm volatile(
        "cp.async.bulk.shared::cluster.global.mbarrier::complete_tx::bytes [%0], [%1], %2, [%3];" ::"r"(dst),
        "l"(src), "r"(bytes), "r"(bar)
        : "memory");
}
__device__ __forceinline__ void tma_2d(uint32_t dst, const CUtensorMap* map, int c0, int c1, uint32_t bar) {
    asm volatile(
        "cp.async.bulk.tensor.2d.shared::cluster.global.mbarrier::complete_tx::bytes [%0], [%1, {%3, %4}], [%2];" ::"r"(dst),
        "l"(map), "r"(bar), "r"(c0), "r"(c1)
        : "memory");
}
__device__ __forceinline__ void ldsm_x4(uint32_t addr, uint32_t& r0, uint32_t& r1, uint32_t& r2, uint32_t& r3) {
    asm volatile("ldmatrix.sync.aligned.m8n8.x4.shared.b16 {%0,%1,%2,%3}, [%4];"
                 : "=r"(r0), "=r"(r1), "=r"(r2), "=r"(r3)
                 : "r"(addr)
                 : "memory");
}
__device__ __forceinline__ void ldsm_x4_t(uint32_t addr, uint32_t& r0, uint32_t& r1, uint32_t& r2, uint32_t& r3) {
    asm volatile("ldmatrix.sync.aligned.m8n8.x4.trans.shared.b16 {%0,%1,%2,%3}, [%4];"
                 : "=r"(r0), "=r"(r1), "=r"(r2), "=r"(r3)
                 : "r"(addr)
                 : "memory");
}
__device__ __forceinline__ void ldsm_x2_t(uint32_t addr, uint32_t& r0, uint32_t& r1) {
    asm volatile("ldmatrix.sync.aligned.m8n8.x2.trans.shared.b16 {%0,%1}, [%2];"
                 : "=r"(r0), "=r"(r1)
                 : "r"(addr)
                 : "memory");
}
__device__ __forceinline__ void mma16816(float (&c)[4], uint32_t a0, uint32_t a1, uint32_t a2, uint32_t a3,
                                         uint32_t b0, uint32_t b1) {
    asm volatile(
        "mma.sync.aligned.m16n8k16.row.col.f32.bf16.bf16.f32 {%0,%1,%2,%3}, {%4,%5,%6,%7}, {%8,%9}, {%0,%1,%2,%3};"
        : "+f"(c[0]), "+f"(c[1]), "+f"(c[2]), "+f"(c[3])
        : "r"(a0), "r"(a1), "r"(a2), "r"(a3), "r"(b0), "r"(b1));
}
__device__ __forceinline__ void mma1688(float (&c)[4], uint32_t a0, uint32_t a1, uint32_t b0) {
    asm volatile("mma.sync.aligned.m16n8k8.row.col.f32.bf16.bf16.f32 {%0,%1,%2,%3}, {%4,%5}, {%6}, {%0,%1,%2,%3};"
                 : "+f"(c[0]), "+f"(c[1]), "+f"(c[2]), "+f"(c[3])
                 : "r"(a0), "r"(a1), "r"(b0));
}
__device__ __forceinline__ void bar_cons() { asm volatile("bar.sync 1, 256;" ::: "memory"); }

__device__ __forceinline__ float bfr(float x) { return __bfloat162float(__float2bfloat16_rn(x)); }
__device__ __forceinline__ uint32_t pack_bf16(float lo, float hi) {
    __nv_bfloat162 v = __floats2bfloat162_rn(lo, hi);
    return *reinterpret_cast<uint32_t*>(&v);
}
__device__ __forceinline__ uint32_t tagw(float v, uint32_t flag) { return (__float_as_uint(v) & ~1u) | flag; }
__device__ __forceinline__ void st_word(uint32_t* p, uint32_t v) {
    asm volatile("st.relaxed.gpu.global.u32 [%0], %1;" ::"l"(p), "r"(v) : "memory");
}
__device__ __forceinline__ void st_word2(uint32_t* p, uint32_t v0, uint32_t v1) {
    asm volatile("st.relaxed.gpu.global.v2.u32 [%0], {%1,%2};" ::"l"(p), "r"(v0), "r"(v1) : "memory");
}
__device__ __forceinline__ void st_word4(uint32_t* p, uint32_t v) {
    asm volatile("st.relaxed.gpu.global.v4.u32 [%0], {%1,%1,%1,%1};" ::"l"(p), "r"(v) : "memory");
}
__device__ __forceinline__ uint32_t ld_word(const uint32_t* p) {
    uint32_t v;
    asm volatile("ld.relaxed.gpu.global.u32 %0, [%1];" : "=r"(v) : "l"(p) : "memory");
    return v;
}
__device__ __forceinline__ uint2 ld_word2(const uint32_t* p) {
    uint2 v;
    asm volatile("ld.relaxed.gpu.global.v2.u32 {%0,%1}, [%2];" : "=r"(v.x), "=r"(v.y) : "l"(p) : "memory");
    return v;
}
__device__ __forceinline__ uint4 ld_word4(const uint32_t* p) {
    uint4 v;
    asm volatile("ld.relaxed.gpu.global.v4.u32 {%0,%1,%2,%3}, [%4];"
                 : "=r"(v.x), "=r"(v.y), "=r"(v.z), "=r"(v.w)
                 : "l"(p)
                 : "memory");
    return v;
}
__device__ __forceinline__ float silu_f(float x) { return x / (1.0f + __expf(-x)); }

template <int KSTEPS, int ASTRIDE>
__device__ __forceinline__ void gemv3_tile(uint32_t wbuf, const __nv_bfloat16* act, int nt, int lane, float (&c)[4]) {
    const int gid = lane >> 2, tig = lane & 3, lm_i = lane & 7, lm_j = lane >> 3;
    const uint32_t wb = wbuf + (8 * lm_j + lm_i) * STR_W3 + nt * 16;
    const __nv_bfloat16* ap = act + (gid & 3) * ASTRIDE + 2 * tig;
    c[0] = c[1] = c[2] = c[3] = 0.f;
#pragma unroll
    for (int kk = 0; kk < KSTEPS / 2; kk++) {
        uint32_t b0, b1, b2, b3;
        ldsm_x4_t(wb + kk * 32 * STR_W3, b0, b1, b2, b3);
        uint32_t a0 = *reinterpret_cast<const uint32_t*>(ap + 32 * kk);
        uint32_t a2 = *reinterpret_cast<const uint32_t*>(ap + 32 * kk + 8);
        uint32_t a4 = *reinterpret_cast<const uint32_t*>(ap + 32 * kk + 16);
        uint32_t a6 = *reinterpret_cast<const uint32_t*>(ap + 32 * kk + 24);
        if (gid >= 4) a0 = a2 = a4 = a6 = 0u;
        mma16816(c, a0, 0u, a2, 0u, b0, b1);
        mma16816(c, a4, 0u, a6, 0u, b2, b3);
    }
}

__global__ void __launch_bounds__(288, 1)
fused_decode_kernel(const __grid_constant__ CUtensorMap kmap, const __grid_constant__ CUtensorMap vmap,
                    const __grid_constant__ CUtensorMap womap, const __grid_constant__ CUtensorMap w2map,
                    const __nv_bfloat16* __restrict__ x, const __nv_bfloat16* __restrict__ wq,
                    const __nv_bfloat16* __restrict__ w1, __nv_bfloat16* __restrict__ out) {
    extern __shared__ uint8_t smem_raw[];
    const uint32_t raw_u32 = smem_u32(smem_raw);
    const uint32_t sbase = (raw_u32 + 1023u) & ~1023u;
    uint8_t* sgen = smem_raw + (sbase - raw_u32);

    const int tid = threadIdx.x, warp = tid >> 5, lane = tid & 31;
    const int cta = blockIdx.x;
    const int g = cta >> 3, r = cta & 7;
    const int b = r >> 1, half = r & 1;

    const uint32_t bar_full = sbase + OFF_BAR;
    const uint32_t bar_empty = sbase + OFF_BAR + 24 * 8;
    const uint32_t bar_s1 = sbase + OFF_BAR + 32 * 8;

    if (tid == 0) {
        TS(0);
        for (int i = 0; i < 32; i++) mbar_init(bar_full + 8 * i, 1);
        mbar_init(bar_s1, 8);
        asm volatile("fence.mbarrier_init.release.cluster;" ::: "memory");
        asm volatile("fence.proxy.async.shared::cta;" ::: "memory");
    }
    __syncthreads();

    const int kv_row0 = (b * kHkv + g) * kSk + (kSk - kWin) + half * 512;

    if (warp == 8) {
        if (lane == 0) {
            asm volatile("prefetch.tensormap [%0];" ::"l"(&kmap) : "memory");
            asm volatile("prefetch.tensormap [%0];" ::"l"(&vmap) : "memory");
            asm volatile("prefetch.tensormap [%0];" ::"l"(&womap) : "memory");
            asm volatile("prefetch.tensormap [%0];" ::"l"(&w2map) : "memory");
        }
#pragma unroll 1
        for (int n = 0; n < 24; n++) {
            const int u = n < 12 ? n : (n < 16 ? n + 8 : n - 4);
            if (n >= kWindow) {
                const int pn = n - kWindow;
                const int pu = pn < 12 ? pn : (pn < 16 ? pn + 8 : pn - 4);
                mbar_wait(bar_full + 8 * pu, 0);
            }
            const uint32_t bar = bar_full + 8 * u;
            if (u < 2) {
                if (lane == 0) mbar_expect_tx(bar, 36 * 512);
                __syncwarp();
                for (int i = 36 * u + lane; i < 36 * u + 36; i += 32)
                    bulk_g2s(sbase + OFF_A + i * STR_WQ, wq + (size_t)(kRows1 * r + i) * kNQ + kQCols * g, 512, bar);
            } else if (u < 4) {
                if (lane == 0) mbar_expect_tx(bar, 36 * 576);
                __syncwarp();
                for (int i = 36 * (u - 2) + lane; i < 36 * (u - 2) + 36; i += 32)
                    bulk_g2s(sbase + OFF_B + i * STR_W1, w1 + (size_t)(kRows1 * r + i) * kF + kHCols * g, 576, bar);
            } else if (u < 20) {
                const int c = (u - 4) & 7;
                if (u >= 12) mbar_wait(bar_empty + 8 * c, 0);
                if (lane == 0) {
                    const CUtensorMap* mp = u >= 12 ? &vmap : &kmap;
                    mbar_expect_tx(bar, kSlotBytes);
                    tma_2d(sbase + OFF_KV + c * kSlotBytes, mp, 0, kv_row0 + kChunkKeys * c, bar);
                    tma_2d(sbase + OFF_KV + c * kSlotBytes + 8192, mp, 64, kv_row0 + kChunkKeys * c, bar);
                }
            } else if (u < 22) {
                if (u == 20) {
                    mbar_wait(bar_s1, 0);
                    if (lane == 0) TS(18);
                }
                if (lane == 0) {
                    mbar_expect_tx(bar, 144 * STR_W3);
                    tma_2d(sbase + OFF_B + (u - 20) * 144 * STR_W3, &w2map, kCols3 * r, kHCols * g + 144 * (u - 20), bar);
                }
            } else {
                if (lane == 0) {
                    mbar_expect_tx(bar, 128 * STR_W3);
                    tma_2d(sbase + OFF_A + (u - 22) * 128 * STR_W3, &womap, kCols3 * r, kQCols * g + 128 * (u - 22), bar);
                }
            }
            __syncwarp();
        }
        return;
    }

    uint32_t epoch;
    asm volatile("ld.relaxed.gpu.global.u32 %0, [%1];" : "=r"(epoch) : "l"(&g_epoch) : "memory");
    uint32_t xw[9];
    if (warp < 4) {
        const uint32_t* xr = reinterpret_cast<const uint32_t*>(x + warp * kD);
#pragma unroll
        for (int i = 0; i < 9; i++) xw[i] = __ldg(xr + lane + 32 * i);
    }
    float x_fin = 0.f;
    if (cta < kFinalCons && tid < 32) {
        const int rc = cta / 9, ntc = cta - 9 * rc;
        x_fin = __bfloat162float(x[(tid >> 3) * kD + kCols3 * rc + 8 * ntc + (tid & 7)]);
    }
    const uint32_t flag = (epoch + 1u) & 1u;

    __nv_bfloat16* xn_s = reinterpret_cast<__nv_bfloat16*>(sgen + OFF_XN);
    __nv_bfloat16* q_s = reinterpret_cast<__nv_bfloat16*>(sgen + OFF_Q);
    __nv_bfloat16* h_s = reinterpret_cast<__nv_bfloat16*>(sgen + OFF_H);
    __nv_bfloat16* o_s = reinterpret_cast<__nv_bfloat16*>(sgen + OFF_O);
    float* ow_s = reinterpret_cast<float*>(sgen + OFF_OW);
    float* ml_s = reinterpret_cast<float*>(sgen + OFF_ML);

    {
        const uint32_t inv = flag ^ 1u;
        st_word4(g_qpart + (size_t)(g * kRanks + r) * kB * kQCols + 4 * tid, inv);
        uint32_t* hd = g_hpart + (size_t)(g * kRanks + r) * kB * kHCols;
        for (int i = tid; i < kB * kHCols / 4; i += 256) st_word4(hd + 4 * i, inv);
        if (tid < 68) st_word4(g_opart + (size_t)((g * kB + b) * 2 + half) * 272 + 4 * tid, inv);
        if (tid >= 96 && tid < 96 + 144) {
            const int i = tid - 96;
            const int nt = i >> 4, wh = (i >> 3) & 1, c4 = i & 7;
            st_word4(g_fpart + (size_t)(((r * 9 + nt) * 2 + wh) * kGroups + g) * 32 + 4 * c4, inv);
        }
    }

    if (warp < 4) {
        float v[18];
        float sum = 0.f;
#pragma unroll
        for (int i = 0; i < 9; i++) {
            v[2 * i] = __uint_as_float(xw[i] << 16);
            v[2 * i + 1] = __uint_as_float(xw[i] & 0xffff0000u);
            sum += v[2 * i] + v[2 * i + 1];
        }
#pragma unroll
        for (int o = 16; o > 0; o >>= 1) sum += __shfl_xor_sync(0xffffffffu, sum, o);
        const float mean = sum * (1.0f / kD);
        float sq = 0.f;
#pragma unroll
        for (int i = 0; i < 18; i++) {
            float d = v[i] - mean;
            sq += d * d;
        }
#pragma unroll
        for (int o = 16; o > 0; o >>= 1) sq += __shfl_xor_sync(0xffffffffu, sq, o);
        const float m_bf = bfr(mean);
        const float v_bf = bfr(sq * (1.0f / kD));
        const float den = bfr(sqrtf(bfr(v_bf + 1e-5f)));
#pragma unroll
        for (int i = 0; i < 9; i++) {
            int e = 2 * (lane + 32 * i) - kRows1 * r;
            if (e >= 0 && e < kRows1) {
                float a0 = bfr(v[2 * i] - m_bf) / den;
                float a1 = bfr(v[2 * i + 1] - m_bf) / den;
                *reinterpret_cast<uint32_t*>(xn_s + warp * 80 + e) = pack_bf16(a0, a1);
            }
        }
    }
    bar_cons();
    if (tid == 0) TS(1);

    const int gid = lane >> 2, tig = lane & 3;
    const int lm_i = lane & 7, lm_j = lane >> 3;

    {
        uint32_t bx[9];
#pragma unroll
        for (int ks = 0; ks < 4; ks++) {
            bx[2 * ks] = gid < 4 ? *reinterpret_cast<const uint32_t*>(xn_s + gid * 80 + 16 * ks + 2 * tig) : 0u;
            bx[2 * ks + 1] = gid < 4 ? *reinterpret_cast<const uint32_t*>(xn_s + gid * 80 + 16 * ks + 8 + 2 * tig) : 0u;
        }
        bx[8] = gid < 4 ? *reinterpret_cast<const uint32_t*>(xn_s + gid * 80 + 64 + 2 * tig) : 0u;

        mbar_wait(bar_full + 8 * 0, 0);
        mbar_wait(bar_full + 8 * 1, 0);
        if (tid == 0) TS(2);
        uint32_t* qdst = g_qpart + (size_t)(g * kRanks + r) * kB * kQCols;
#pragma unroll
        for (int t = 0; t < 2; t++) {
            const int m0 = 16 * (warp + 8 * t);
            float c[4] = {0.f, 0.f, 0.f, 0.f};
            const uint32_t abase = sbase + OFF_A + (lm_i + (lm_j >> 1) * 8) * STR_WQ + (m0 + (lm_j & 1) * 8) * 2;
#pragma unroll
            for (int ks = 0; ks < 4; ks++) {
                uint32_t a0, a1, a2, a3;
                ldsm_x4_t(abase + ks * 16 * STR_WQ, a0, a1, a2, a3);
                mma16816(c, a0, a1, a2, a3, bx[2 * ks], bx[2 * ks + 1]);
            }
            {
                uint32_t a0, a1;
                ldsm_x2_t(sbase + OFF_A + (64 + lm_i) * STR_WQ + (m0 + (lm_j & 1) * 8) * 2, a0, a1);
                mma1688(c, a0, a1, bx[8]);
            }
            if (tig < 2) {
                const int col = m0 + gid;
                st_word(qdst + (2 * tig) * kQCols + col, tagw(c[0], flag));
                st_word(qdst + (2 * tig + 1) * kQCols + col, tagw(c[1], flag));
                st_word(qdst + (2 * tig) * kQCols + col + 8, tagw(c[2], flag));
                st_word(qdst + (2 * tig + 1) * kQCols + col + 8, tagw(c[3], flag));
            }
        }
        mbar_wait(bar_full + 8 * 2, 0);
        mbar_wait(bar_full + 8 * 3, 0);
        if (tid == 0) TS(3);
        uint32_t* hdst = g_hpart + (size_t)(g * kRanks + r) * kB * kHCols;
        for (int t = warp; t < 18; t += 8) {
            const int m0 = 16 * t;
            float c[4] = {0.f, 0.f, 0.f, 0.f};
            const uint32_t abase = sbase + OFF_B + (lm_i + (lm_j >> 1) * 8) * STR_W1 + (m0 + (lm_j & 1) * 8) * 2;
#pragma unroll
            for (int ks = 0; ks < 4; ks++) {
                uint32_t a0, a1, a2, a3;
                ldsm_x4_t(abase + ks * 16 * STR_W1, a0, a1, a2, a3);
                mma16816(c, a0, a1, a2, a3, bx[2 * ks], bx[2 * ks + 1]);
            }
            {
                uint32_t a0, a1;
                ldsm_x2_t(sbase + OFF_B + (64 + lm_i) * STR_W1 + (m0 + (lm_j & 1) * 8) * 2, a0, a1);
                mma1688(c, a0, a1, bx[8]);
            }
            if (tig < 2) {
                const int col = m0 + gid;
                st_word(hdst + (2 * tig) * kHCols + col, tagw(c[0], flag));
                st_word(hdst + (2 * tig + 1) * kHCols + col, tagw(c[1], flag));
                st_word(hdst + (2 * tig) * kHCols + col + 8, tagw(c[2], flag));
                st_word(hdst + (2 * tig + 1) * kHCols + col + 8, tagw(c[3], flag));
            }
        }
    }
    __syncwarp();
    if (lane == 0) mbar_arrive(bar_s1);

    {
        const uint32_t* src = g_qpart + (size_t)(g * kRanks) * kB * kQCols + b * kQCols + tid;
        uint32_t w[8];
        for (int it = 0; it < kSpinLimit; it++) {
            uint32_t bad = 0;
#pragma unroll
            for (int p = 0; p < 8; p++) {
                w[p] = ld_word(src + p * kB * kQCols);
                bad |= (w[p] ^ flag);
            }
            if (!(bad & 1u)) break;
        }
        float s = 0.f;
#pragma unroll
        for (int p = 0; p < 8; p++) s += __uint_as_float(w[p]);
        q_s[(tid >> 7) * 136 + (tid & 127)] = __float2bfloat16_rn(s);
    }
    bar_cons();
    if (tid == 0) TS(4);

    const uint32_t slot = sbase + OFF_KV + warp * kSlotBytes;
    float mx, lsum = 0.f;
    uint32_t pb[8];
    {
        uint32_t qa[16];
#pragma unroll
        for (int j = 0; j < 8; j++) {
            qa[2 * j] = gid < 2 ? *reinterpret_cast<const uint32_t*>(q_s + gid * 136 + 16 * j + 2 * tig) : 0u;
            qa[2 * j + 1] = gid < 2 ? *reinterpret_cast<const uint32_t*>(q_s + gid * 136 + 16 * j + 8 + 2 * tig) : 0u;
        }
        mbar_wait(bar_full + 8 * (4 + warp), 0);
        if (tid == 0) TS(5);
        if (tid == 224) TS(7);
        float sc[8][4];
#pragma unroll
        for (int nt = 0; nt < 8; nt++) {
            sc[nt][0] = sc[nt][1] = sc[nt][2] = sc[nt][3] = 0.f;
#pragma unroll
            for (int kk = 0; kk < 4; kk++) {
                const int cg = 4 * kk + lm_j;
                const uint32_t addr =
                    slot + (cg >> 3) * 8192 + (8 * nt + lm_i) * 128 + (((cg & 7) ^ lm_i) << 4);
                uint32_t b0, b1, b2, b3;
                ldsm_x4(addr, b0, b1, b2, b3);
                mma16816(sc[nt], qa[4 * kk], 0u, qa[4 * kk + 1], 0u, b0, b1);
                mma16816(sc[nt], qa[4 * kk + 2], 0u, qa[4 * kk + 3], 0u, b2, b3);
            }
        }
        mx = -INFINITY;
        const float scale = 0.08838834764831845f;
#pragma unroll
        for (int nt = 0; nt < 8; nt++) {
            sc[nt][0] = bfr(bfr(sc[nt][0]) * scale);
            sc[nt][1] = bfr(bfr(sc[nt][1]) * scale);
            mx = fmaxf(mx, fmaxf(sc[nt][0], sc[nt][1]));
        }
        __syncwarp();
        if (lane == 0) mbar_arrive(bar_empty + 8 * warp);
        mx = fmaxf(mx, __shfl_xor_sync(0xffffffffu, mx, 1));
        mx = fmaxf(mx, __shfl_xor_sync(0xffffffffu, mx, 2));
        const float l2e = 1.4426950408889634f;
#pragma unroll
        for (int nt = 0; nt < 8; nt++) {
            float p0 = exp2f((sc[nt][0] - mx) * l2e);
            float p1 = exp2f((sc[nt][1] - mx) * l2e);
            lsum += p0 + p1;
            pb[nt] = pack_bf16(p0, p1);
        }
        lsum += __shfl_xor_sync(0xffffffffu, lsum, 1);
        lsum += __shfl_xor_sync(0xffffffffu, lsum, 2);
    }

    {
        for (int idx = tid; idx < kB * kHCols / 4; idx += 256) {
            const uint32_t* src = g_hpart + (size_t)(g * kRanks) * kB * kHCols + 4 * idx;
            uint4 w[8];
            for (int it = 0; it < kSpinLimit; it++) {
                uint32_t bad = 0;
#pragma unroll
                for (int p = 0; p < 8; p++) {
                    w[p] = ld_word4(src + p * kB * kHCols);
                    bad |= (w[p].x ^ flag) | (w[p].y ^ flag) | (w[p].z ^ flag) | (w[p].w ^ flag);
                }
                if (!(bad & 1u)) break;
            }
            float s0 = 0.f, s1 = 0.f, s2 = 0.f, s3 = 0.f;
#pragma unroll
            for (int p = 0; p < 8; p++) {
                s0 += __uint_as_float(w[p].x);
                s1 += __uint_as_float(w[p].y);
                s2 += __uint_as_float(w[p].z);
                s3 += __uint_as_float(w[p].w);
            }
            const int bb = idx / 72, c4 = idx - bb * 72;
            uint2 pk;
            pk.x = pack_bf16(silu_f(bfr(s0)), silu_f(bfr(s1)));
            pk.y = pack_bf16(silu_f(bfr(s2)), silu_f(bfr(s3)));
            *reinterpret_cast<uint2*>(h_s + bb * 296 + 4 * c4) = pk;
        }
        bar_cons();
        if (tid == 0) TS(10);
        mbar_wait(bar_full + 8 * 20, 0);
        mbar_wait(bar_full + 8 * 21, 0);
        if (tid == 0) TS(11);
        for (int nt = warp; nt < 9; nt += 8) {
            float c[4];
            gemv3_tile<18, 296>(sbase + OFF_B, h_s, nt, lane, c);
            if (gid < 4)
                st_word2(g_fpart + (size_t)(((r * 9 + nt) * 2 + 1) * kGroups + g) * 32 + gid * 8 + 2 * tig,
                         tagw(c[0], flag), tagw(c[1], flag));
        }
        if (tid == 0) TS(12);
    }

    {
        mbar_wait(bar_full + 8 * (12 + warp), 0);
        if (tid == 0) TS(6);
        if (tid == 224) TS(8);
#pragma unroll
        for (int mt = 0; mt < 8; mt++) {
            float oc[4] = {0.f, 0.f, 0.f, 0.f};
            const int cg = 2 * mt + (lm_j & 1);
#pragma unroll
            for (int ks = 0; ks < 4; ks++) {
                const int key = 16 * ks + (lm_j >> 1) * 8 + lm_i;
                const uint32_t addr = slot + (cg >> 3) * 8192 + key * 128 + (((cg & 7) ^ lm_i) << 4);
                uint32_t a0, a1, a2, a3;
                ldsm_x4_t(addr, a0, a1, a2, a3);
                mma16816(oc, a0, a1, a2, a3, pb[2 * ks], pb[2 * ks + 1]);
            }
            if (tig == 0) {
                const int d = 16 * mt + gid;
                ow_s[warp * 256 + d] = oc[0];
                ow_s[warp * 256 + 128 + d] = oc[1];
                ow_s[warp * 256 + d + 8] = oc[2];
                ow_s[warp * 256 + 128 + d + 8] = oc[3];
            }
        }
        if (lane == 0 || lane == 4) {
            ml_s[warp * 4 + (lane >> 2) * 2] = mx;
            ml_s[warp * 4 + (lane >> 2) * 2 + 1] = lsum;
        }
    }
    bar_cons();
    if (tid == 0) TS(13);

    {
        const int head = tid >> 7;
        float M = -INFINITY;
#pragma unroll
        for (int w = 0; w < 8; w++) M = fmaxf(M, ml_s[w * 4 + head * 2]);
        float L = 0.f, O = 0.f;
#pragma unroll
        for (int w = 0; w < 8; w++) {
            const float wgt = exp2f((ml_s[w * 4 + head * 2] - M) * 1.4426950408889634f);
            L += wgt * ml_s[w * 4 + head * 2 + 1];
            O += wgt * ow_s[w * 256 + tid];
        }
        uint32_t* od = g_opart + (size_t)((g * kB + b) * 2 + half) * 272 + head * 136;
        st_word(od + (tid & 127), tagw(O, flag));
        if ((tid & 127) == 0) st_word2(od + 128, tagw(M, flag), tagw(L, flag));

        const uint32_t* src = g_opart + (size_t)(g * kB * 2) * 272 + head * 136;
        uint32_t wv[8];
        uint2 wml[8];
        for (int it = 0; it < kSpinLimit; it++) {
            uint32_t bad = 0;
#pragma unroll
            for (int p = 0; p < 8; p++) {
                wv[p] = ld_word(src + p * 272 + (tid & 127));
                wml[p] = ld_word2(src + p * 272 + 128);
                bad |= (wv[p] ^ flag) | (wml[p].x ^ flag) | (wml[p].y ^ flag);
            }
            if (!(bad & 1u)) break;
        }
#pragma unroll
        for (int bb = 0; bb < 4; bb++) {
            const float m0 = __uint_as_float(wml[2 * bb].x), m1 = __uint_as_float(wml[2 * bb + 1].x);
            const float MM = fmaxf(m0, m1);
            const float e0 = exp2f((m0 - MM) * 1.4426950408889634f), e1 = exp2f((m1 - MM) * 1.4426950408889634f);
            const float LL = e0 * __uint_as_float(wml[2 * bb].y) + e1 * __uint_as_float(wml[2 * bb + 1].y);
            const float OO = e0 * __uint_as_float(wv[2 * bb]) + e1 * __uint_as_float(wv[2 * bb + 1]);
            o_s[bb * 264 + tid] = __float2bfloat16_rn(OO / LL);
        }
    }
    bar_cons();
    if (tid == 0) TS(9);

    {
        mbar_wait(bar_full + 8 * 22, 0);
        mbar_wait(bar_full + 8 * 23, 0);
        if (tid == 0) TS(14);
        for (int nt = warp; nt < 9; nt += 8) {
            float c[4];
            gemv3_tile<16, 264>(sbase + OFF_A, o_s, nt, lane, c);
            if (gid < 4)
                st_word2(g_fpart + (size_t)(((r * 9 + nt) * 2 + 0) * kGroups + g) * 32 + gid * 8 + 2 * tig,
                         tagw(c[0], flag), tagw(c[1], flag));
        }
    }
    if (tid == 0) TS(15);

    if (cta < kFinalCons) {
        float4* red = reinterpret_cast<float4*>(sgen + OFF_RED);
        {
            const uint32_t* src = g_fpart + (size_t)cta * 1024 + 4 * tid;
            uint4 w;
            for (int it = 0; it < kSpinLimit; it++) {
                w = ld_word4(src);
                const uint32_t bad = (w.x ^ flag) | (w.y ^ flag) | (w.z ^ flag) | (w.w ^ flag);
                if (!(bad & 1u)) break;
            }
            float4 s = make_float4(__uint_as_float(w.x), __uint_as_float(w.y), __uint_as_float(w.z),
                                   __uint_as_float(w.w));
#pragma unroll
            for (int o = 8; o <= 16; o <<= 1) {
                s.x += __shfl_xor_sync(0xffffffffu, s.x, o);
                s.y += __shfl_xor_sync(0xffffffffu, s.y, o);
                s.z += __shfl_xor_sync(0xffffffffu, s.z, o);
                s.w += __shfl_xor_sync(0xffffffffu, s.w, o);
            }
            if (lane < 8) red[warp * 8 + lane] = s;
        }
        bar_cons();
        if (tid == 0) TS(16);
        if (tid < 32) {
            const float* rf = reinterpret_cast<const float*>(red);
            float sv = 0.f, gv = 0.f;
#pragma unroll
            for (int w = 0; w < 4; w++) {
                sv += rf[w * 32 + tid];
                gv += rf[(4 + w) * 32 + tid];
            }
            const int rc = cta / 9, ntc = cta - 9 * rc;
            const float gg = bfr(silu_f(bfr(gv)));
            const float sg = bfr(bfr(sv) * gg);
            out[(tid >> 3) * kD + kCols3 * rc + 8 * ntc + (tid & 7)] = __float2bfloat16_rn(x_fin + sg);
        }
        if (tid == 0) TS(17);
        if (cta == 0 && tid == 0) {
            asm volatile("st.relaxed.gpu.global.u32 [%0], %1;" ::"l"(&g_epoch), "r"(epoch + 1u) : "memory");
        }
    }
}

typedef CUresult (*PFN_encodeTiled)(CUtensorMap*, CUtensorMapDataType, cuuint32_t, void*, const cuuint64_t*,
                                    const cuuint64_t*, const cuuint32_t*, const cuuint32_t*, CUtensorMapInterleave,
                                    CUtensorMapSwizzle, CUtensorMapL2promotion, CUtensorMapFloatOOBfill);

void make_map(PFN_encodeTiled enc, CUtensorMap* map, const void* ptr, uint64_t cols, uint64_t rows, uint32_t box_c,
              uint32_t box_r, CUtensorMapSwizzle swz, CUtensorMapL2promotion promo) {
    cuuint64_t gdim[2] = {cols, rows};
    cuuint64_t gstr[1] = {cols * 2};
    cuuint32_t box[2] = {box_c, box_r};
    cuuint32_t estr[2] = {1, 1};
    enc(map, CU_TENSOR_MAP_DATA_TYPE_BFLOAT16, 2, const_cast<void*>(ptr), gdim, gstr, box, estr,
        CU_TENSOR_MAP_INTERLEAVE_NONE, swz, promo, CU_TENSOR_MAP_FLOAT_OOB_FILL_NONE);
}

}

extern "C" void kernel_launch(void* const* d_in, const int* in_sizes, int n_in, void* d_out, int out_size) {
    (void)in_sizes;
    (void)n_in;
    (void)out_size;
    static PFN_encodeTiled enc = nullptr;
    if (!enc) {
        void* fn = nullptr;
        cudaDriverEntryPointQueryResult st;
        cudaGetDriverEntryPoint("cuTensorMapEncodeTiled", &fn, cudaEnableDefault, &st);
        enc = (PFN_encodeTiled)fn;
        cudaFuncSetAttribute(fused_decode_kernel, cudaFuncAttributeMaxDynamicSharedMemorySize, SMEM_BYTES);
    }
    CUtensorMap kmap, vmap, womap, w2map;
    make_map(enc, &kmap, d_in[1], kDh, (uint64_t)kB * kHkv * kSk, 64, kChunkKeys, CU_TENSOR_MAP_SWIZZLE_128B,
             CU_TENSOR_MAP_L2_PROMOTION_L2_256B);
    make_map(enc, &vmap, d_in[2], kDh, (uint64_t)kB * kHkv * kSk, 64, kChunkKeys, CU_TENSOR_MAP_SWIZZLE_128B,
             CU_TENSOR_MAP_L2_PROMOTION_L2_256B);
    make_map(enc, &womap, d_in[4], kD, kNQ, kCols3, 128, CU_TENSOR_MAP_SWIZZLE_NONE,
             CU_TENSOR_MAP_L2_PROMOTION_L2_128B);
    make_map(enc, &w2map, d_in[7], kD, kF, kCols3, 144, CU_TENSOR_MAP_SWIZZLE_NONE,
             CU_TENSOR_MAP_L2_PROMOTION_L2_128B);
    fused_decode_kernel<<<kCTAs, 288, SMEM_BYTES>>>(kmap, vmap, womap, w2map, (const __nv_bfloat16*)d_in[0],
                                                    (const __nv_bfloat16*)d_in[3], (const __nv_bfloat16*)d_in[6],
                                                    (__nv_bfloat16*)d_out);
}
```

```cpp
#include <cuda_runtime.h>
#include <cuda_bf16.h>
#include <cuda.h>
#include <stdint.h>

namespace {

constexpr int kB = 4, kD = 576, kHkv = 16, kSk = 4096, kDh = 128, kWin = 1024, kF = 4608;
constexpr int kNQ = 4096;
constexpr int kGroups = 16, kRanks = 8, kCTAs = 128;
constexpr int kRows1 = 72;
constexpr int kQCols = 256, kHCols = 288;
constexpr int kCols3 = 72;
constexpr int kChunkKeys = 64;
constexpr int kFinalCons = 72;

constexpr int kSlotBytes = 16384;
constexpr int OFF_KV = 0;
constexpr int STR_W3 = 144;
constexpr int BOX_WQ = kRows1 * 128;
constexpr int BOX_W1 = kRows1 * 144;
constexpr int OFF_A = 8 * kSlotBytes;
constexpr int SZ_A = 4 * BOX_WQ;
constexpr int OFF_B = OFF_A + SZ_A;
constexpr int SZ_B = 4 * BOX_W1;
constexpr int OFF_XN = OFF_B + SZ_B;
constexpr int OFF_Q = OFF_XN + 640;
constexpr int OFF_H = OFF_Q + 544;
constexpr int OFF_O = OFF_H + 4 * 296 * 2;
constexpr int OFF_OW = OFF_O + 4 * 264 * 2;
constexpr int OFF_ML = OFF_OW + 8 * 256 * 4;
constexpr int OFF_RED = OFF_ML + 128;
constexpr int OFF_BAR = OFF_RED + 1024;
constexpr int SMEM_USED = OFF_BAR + 288;
constexpr int SMEM_BYTES = SMEM_USED + 1024;

static_assert(OFF_A % 128 == 0 && OFF_B % 128 == 0, "align");
static_assert(OFF_OW % 16 == 0 && OFF_RED % 16 == 0, "align");
static_assert(OFF_BAR % 8 == 0, "align");
static_assert(SMEM_BYTES <= 232448, "smem");

__device__ __align__(128) uint32_t g_qpart[kGroups * kRanks * kB * kQCols];
__device__ __align__(128) uint32_t g_hpart[kGroups * kRanks * kB * kHCols];
__device__ __align__(128) uint32_t g_opart[kGroups * kB * 2 * 2 * 136];
__device__ __align__(128) uint32_t g_fpart[kFinalCons * 2 * kGroups * 32];
__device__ uint32_t g_epoch;

constexpr int kSpinLimit = 1 << 22;
#define KWINDOW 4
constexpr int kWindow = KWINDOW;

#define ORDER 1
__constant__ int c_order[24] = {0, 1, 2, 3, 4, 5, 6, 7, 8, 9, 10, 11, 20, 21, 22, 23, 12, 13, 14, 15, 16, 17, 18, 19};

#define TS(k)
#define TS2(k)

__device__ __forceinline__ uint32_t smem_u32(const void* p) {
    return (uint32_t)__cvta_generic_to_shared(p);
}
__device__ __forceinline__ void mbar_init(uint32_t bar, uint32_t count) {
    asm volatile("mbarrier.init.shared::cta.b64 [%0], %1;" ::"r"(bar), "r"(count) : "memory");
}
__device__ __forceinline__ void mbar_expect_tx(uint32_t bar, uint32_t bytes) {
    asm volatile("mbarrier.arrive.expect_tx.shared::cta.b64 _, [%0], %1;" ::"r"(bar), "r"(bytes) : "memory");
}
__device__ __forceinline__ void mbar_arrive(uint32_t bar) {
    asm volatile("mbarrier.arrive.shared::cta.b64 _, [%0];" ::"r"(bar) : "memory");
}
__device__ __forceinline__ bool mbar_try_wait(uint32_t bar, uint32_t parity) {
    uint32_t ok;
    asm volatile(
        "{\n .reg .pred p;\n mbarrier.try_wait.parity.shared::cta.b64 p, [%1], %2;\n selp.u32 %0, 1, 0, p;\n}"
        : "=r"(ok)
        : "r"(bar), "r"(parity)
        : "memory");
    return ok != 0;
}
__device__ __forceinline__ void mbar_wait(uint32_t bar, uint32_t parity) {
    for (int i = 0; i < kSpinLimit; i++) {
        if (mbar_try_wait(bar, parity)) break;
    }
}
__device__ __forceinline__ void bulk_g2s(uint32_t dst, const void* src, uint32_t bytes, uint32_t bar) {
    asm volatile(
        "cp.async.bulk.shared::cluster.global.mbarrier::complete_tx::bytes [%0], [%1], %2, [%3];" ::"r"(dst),
        "l"(src), "r"(bytes), "r"(bar)
        : "memory");
}
__device__ __forceinline__ void tma_2d(uint32_t dst, const CUtensorMap* map, int c0, int c1, uint32_t bar) {
    asm volatile(
        "cp.async.bulk.tensor.2d.shared::cluster.global.mbarrier::complete_tx::bytes [%0], [%1, {%3, %4}], [%2];" ::"r"(dst),
        "l"(map), "r"(bar), "r"(c0), "r"(c1)
        : "memory");
}
__device__ __forceinline__ void ldsm_x4(uint32_t addr, uint32_t& r0, uint32_t& r1, uint32_t& r2, uint32_t& r3) {
    asm volatile("ldmatrix.sync.aligned.m8n8.x4.shared.b16 {%0,%1,%2,%3}, [%4];"
                 : "=r"(r0), "=r"(r1), "=r"(r2), "=r"(r3)
                 : "r"(addr)
                 : "memory");
}
__device__ __forceinline__ void ldsm_x4_t(uint32_t addr, uint32_t& r0, uint32_t& r1, uint32_t& r2, uint32_t& r3) {
    asm volatile("ldmatrix.sync.aligned.m8n8.x4.trans.shared.b16 {%0,%1,%2,%3}, [%4];"
                 : "=r"(r0), "=r"(r1), "=r"(r2), "=r"(r3)
                 : "r"(addr)
                 : "memory");
}
__device__ __forceinline__ void ldsm_x2_t(uint32_t addr, uint32_t& r0, uint32_t& r1) {
    asm volatile("ldmatrix.sync.aligned.m8n8.x2.trans.shared.b16 {%0,%1}, [%2];"
                 : "=r"(r0), "=r"(r1)
                 : "r"(addr)
                 : "memory");
}
__device__ __forceinline__ void mma16816(float (&c)[4], uint32_t a0, uint32_t a1, uint32_t a2, uint32_t a3,
                                         uint32_t b0, uint32_t b1) {
    asm volatile(
        "mma.sync.aligned.m16n8k16.row.col.f32.bf16.bf16.f32 {%0,%1,%2,%3}, {%4,%5,%6,%7}, {%8,%9}, {%0,%1,%2,%3};"
        : "+f"(c[0]), "+f"(c[1]), "+f"(c[2]), "+f"(c[3])
        : "r"(a0), "r"(a1), "r"(a2), "r"(a3), "r"(b0), "r"(b1));
}
__device__ __forceinline__ void mma1688(float (&c)[4], uint32_t a0, uint32_t a1, uint32_t b0) {
    asm volatile("mma.sync.aligned.m16n8k8.row.col.f32.bf16.bf16.f32 {%0,%1,%2,%3}, {%4,%5}, {%6}, {%0,%1,%2,%3};"
                 : "+f"(c[0]), "+f"(c[1]), "+f"(c[2]), "+f"(c[3])
                 : "r"(a0), "r"(a1), "r"(b0));
}
__device__ __forceinline__ void bar_cons() { asm volatile("bar.sync 1, 256;" ::: "memory"); }

__device__ __forceinline__ float bfr(float x) { return __bfloat162float(__float2bfloat16_rn(x)); }
__device__ __forceinline__ uint32_t pack_bf16(float lo, float hi) {
    __nv_bfloat162 v = __floats2bfloat162_rn(lo, hi);
    return *reinterpret_cast<uint32_t*>(&v);
}
__device__ __forceinline__ uint32_t tagw(float v, uint32_t flag) { return (__float_as_uint(v) & ~1u) | flag; }
__device__ __forceinline__ void st_word(uint32_t* p, uint32_t v) {
    asm volatile("st.relaxed.gpu.global.u32 [%0], %1;" ::"l"(p), "r"(v) : "memory");
}
__device__ __forceinline__ void st_word2(uint32_t* p, uint32_t v0, uint32_t v1) {
    asm volatile("st.relaxed.gpu.global.v2.u32 [%0], {%1,%2};" ::"l"(p), "r"(v0), "r"(v1) : "memory");
}
__device__ __forceinline__ void st_word4(uint32_t* p, uint32_t v) {
    asm volatile("st.relaxed.gpu.global.v4.u32 [%0], {%1,%1,%1,%1};" ::"l"(p), "r"(v) : "memory");
}
__device__ __forceinline__ uint32_t ld_word(const uint32_t* p) {
    uint32_t v;
    asm volatile("ld.relaxed.gpu.global.u32 %0, [%1];" : "=r"(v) : "l"(p) : "memory");
    return v;
}
__device__ __forceinline__ uint2 ld_word2(const uint32_t* p) {
    uint2 v;
    asm volatile("ld.relaxed.gpu.global.v2.u32 {%0,%1}, [%2];" : "=r"(v.x), "=r"(v.y) : "l"(p) : "memory");
    return v;
}
__device__ __forceinline__ uint4 ld_word4(const uint32_t* p) {
    uint4 v;
    asm volatile("ld.relaxed.gpu.global.v4.u32 {%0,%1,%2,%3}, [%4];"
                 : "=r"(v.x), "=r"(v.y), "=r"(v.z), "=r"(v.w)
                 : "l"(p)
                 : "memory");
    return v;
}
__device__ __forceinline__ float silu_f(float x) { return x / (1.0f + __expf(-x)); }

template <int KSTEPS, int ASTRIDE>
__device__ __forceinline__ void gemv3_tile(uint32_t wbuf, const __nv_bfloat16* act, int nt, int lane, float (&c)[4]) {
    const int gid = lane >> 2, tig = lane & 3, lm_i = lane & 7, lm_j = lane >> 3;
    const uint32_t wb = wbuf + (8 * lm_j + lm_i) * STR_W3 + nt * 16;
    const __nv_bfloat16* ap = act + (gid & 3) * ASTRIDE + 2 * tig;
    float acc[4][4];
#pragma unroll
    for (int i = 0; i < 4; i++) acc[i][0] = acc[i][1] = acc[i][2] = acc[i][3] = 0.f;
#pragma unroll
    for (int kk = 0; kk < KSTEPS / 2; kk++) {
        uint32_t b0, b1, b2, b3;
        ldsm_x4_t(wb + kk * 32 * STR_W3, b0, b1, b2, b3);
        uint32_t a0 = *reinterpret_cast<const uint32_t*>(ap + 32 * kk);
        uint32_t a2 = *reinterpret_cast<const uint32_t*>(ap + 32 * kk + 8);
        uint32_t a4 = *reinterpret_cast<const uint32_t*>(ap + 32 * kk + 16);
        uint32_t a6 = *reinterpret_cast<const uint32_t*>(ap + 32 * kk + 24);
        if (gid >= 4) a0 = a2 = a4 = a6 = 0u;
        mma16816(acc[(2 * kk) & 3], a0, 0u, a2, 0u, b0, b1);
        mma16816(acc[(2 * kk + 1) & 3], a4, 0u, a6, 0u, b2, b3);
    }
    c[0] = (acc[0][0] + acc[1][0]) + (acc[2][0] + acc[3][0]);
    c[1] = (acc[0][1] + acc[1][1]) + (acc[2][1] + acc[3][1]);
    c[2] = c[3] = 0.f;
}

__global__ void __launch_bounds__(288, 1)
fused_decode_kernel(const __grid_constant__ CUtensorMap kmap, const __grid_constant__ CUtensorMap vmap,
                    const __grid_constant__ CUtensorMap womap, const __grid_constant__ CUtensorMap w2map,
                    const __grid_constant__ CUtensorMap wqmap, const __grid_constant__ CUtensorMap w1map,
                    const __nv_bfloat16* __restrict__ x, __nv_bfloat16* __restrict__ out) {
    extern __shared__ uint8_t smem_raw[];
    const uint32_t raw_u32 = smem_u32(smem_raw);
    const uint32_t sbase = (raw_u32 + 1023u) & ~1023u;
    uint8_t* sgen = smem_raw + (sbase - raw_u32);

    const int tid = threadIdx.x, warp = tid >> 5, lane = tid & 31;
    const int cta = blockIdx.x;
    const int g = cta >> 3, r = cta & 7;
    const int b = r >> 1, half = r & 1;

    const uint32_t bar_full = sbase + OFF_BAR;
    const uint32_t bar_empty = sbase + OFF_BAR + 24 * 8;
    const uint32_t bar_s1 = sbase + OFF_BAR + 32 * 8;

    const int kv_row0 = (b * kHkv + g) * kSk + (kSk - kWin) + half * 512;

    if (warp == 8) {
        if (lane == 0) {
            TS(0);
            for (int i = 0; i < 32; i++) mbar_init(bar_full + 8 * i, 1);
            mbar_init(bar_s1, 8);
            asm volatile("fence.mbarrier_init.release.cluster;" ::: "memory");
            asm volatile("fence.proxy.async.shared::cta;" ::: "memory");
        }
        __syncwarp();
        asm volatile("bar.arrive 2, 288;" ::: "memory");
#pragma unroll 1
        for (int n = 0; n < 24; n++) {
            const int u = c_order[n];
            if (n >= kWindow) mbar_wait(bar_full + 8 * c_order[n - kWindow], 0);
            const uint32_t bar = bar_full + 8 * u;
            if (u < 2) {
                if (lane == 0) {
                    mbar_expect_tx(bar, 2 * BOX_WQ);
                    tma_2d(sbase + OFF_A + (2 * u) * BOX_WQ, &wqmap, kQCols * g + 128 * u, kRows1 * r, bar);
                    tma_2d(sbase + OFF_A + (2 * u + 1) * BOX_WQ, &wqmap, kQCols * g + 128 * u + 64, kRows1 * r, bar);
                }
            } else if (u < 4) {
                if (lane == 0) {
                    mbar_expect_tx(bar, 2 * BOX_W1);
                    tma_2d(sbase + OFF_B + (2 * u - 4) * BOX_W1, &w1map, kHCols * g + 144 * (u - 2), kRows1 * r, bar);
                    tma_2d(sbase + OFF_B + (2 * u - 3) * BOX_W1, &w1map, kHCols * g + 144 * (u - 2) + 72, kRows1 * r, bar);
                }
            } else if (u < 20) {
                const int c = (u - 4) & 7;
                if (u >= 12) mbar_wait(bar_empty + 8 * c, 0);
                if (lane == 0) {
                    const CUtensorMap* mp = u >= 12 ? &vmap : &kmap;
                    mbar_expect_tx(bar, kSlotBytes);
                    tma_2d(sbase + OFF_KV + c * kSlotBytes, mp, 0, kv_row0 + kChunkKeys * c, bar);
                    tma_2d(sbase + OFF_KV + c * kSlotBytes + 8192, mp, 64, kv_row0 + kChunkKeys * c, bar);
                }
            } else if (u < 22) {
                mbar_wait(bar_s1, 0);
                if (lane == 0) {
                    mbar_expect_tx(bar, 144 * STR_W3);
                    tma_2d(sbase + OFF_B + (u - 20) * 144 * STR_W3, &w2map, kCols3 * r, kHCols * g + 144 * (u - 20), bar);
                }
            } else {
                mbar_wait(bar_s1, 0);
                if (lane == 0) {
                    mbar_expect_tx(bar, 128 * STR_W3);
                    tma_2d(sbase + OFF_A + (u - 22) * 128 * STR_W3, &womap, kCols3 * r, kQCols * g + 128 * (u - 22), bar);
                }
            }
            if (lane == 0) TS2(n);
            __syncwarp();
        }
        return;
    }

    uint32_t epoch;
    asm volatile("ld.relaxed.gpu.global.u32 %0, [%1];" : "=r"(epoch) : "l"(&g_epoch) : "memory");
    uint32_t xw[9];
    if (warp < 4) {
        const uint32_t* xr = reinterpret_cast<const uint32_t*>(x + warp * kD);
#pragma unroll
        for (int i = 0; i < 9; i++) xw[i] = __ldg(xr + lane + 32 * i);
    }
    float x_fin = 0.f;
    if (cta < kFinalCons && tid < 32) {
        const int rc = cta / 9, ntc = cta - 9 * rc;
        x_fin = __bfloat162float(x[(tid >> 3) * kD + kCols3 * rc + 8 * ntc + (tid & 7)]);
    }
    const uint32_t flag = (epoch + 1u) & 1u;

    __nv_bfloat16* xn_s = reinterpret_cast<__nv_bfloat16*>(sgen + OFF_XN);
    __nv_bfloat16* q_s = reinterpret_cast<__nv_bfloat16*>(sgen + OFF_Q);
    __nv_bfloat16* h_s = reinterpret_cast<__nv_bfloat16*>(sgen + OFF_H);
    __nv_bfloat16* o_s = reinterpret_cast<__nv_bfloat16*>(sgen + OFF_O);
    float* ow_s = reinterpret_cast<float*>(sgen + OFF_OW);
    float* ml_s = reinterpret_cast<float*>(sgen + OFF_ML);

    {
        const uint32_t inv = flag ^ 1u;
        st_word4(g_qpart + (size_t)(g * kRanks + r) * kB * kQCols + 4 * tid, inv);
        uint32_t* hd = g_hpart + (size_t)(g * kRanks + r) * kB * kHCols;
        for (int i = tid; i < kB * kHCols / 4; i += 256) st_word4(hd + 4 * i, inv);
        if (tid < 68) st_word4(g_opart + (size_t)((g * kB + b) * 2 + half) * 272 + 4 * tid, inv);
        if (tid >= 96 && tid < 96 + 144) {
            const int i = tid - 96;
            const int nt = i >> 4, wh = (i >> 3) & 1, c4 = i & 7;
            st_word4(g_fpart + (size_t)(((r * 9 + nt) * 2 + wh) * kGroups + g) * 32 + 4 * c4, inv);
        }
    }

    if (warp < 4) {
        float v[18];
        float sum = 0.f;
#pragma unroll
        for (int i = 0; i < 9; i++) {
            v[2 * i] = __uint_as_float(xw[i] << 16);
            v[2 * i + 1] = __uint_as_float(xw[i] & 0xffff0000u);
            sum += v[2 * i] + v[2 * i + 1];
        }
#pragma unroll
        for (int o = 16; o > 0; o >>= 1) sum += __shfl_xor_sync(0xffffffffu, sum, o);
        const float mean = sum * (1.0f / kD);
        float sq = 0.f;
#pragma unroll
        for (int i = 0; i < 18; i++) {
            float d = v[i] - mean;
            sq += d * d;
        }
#pragma unroll
        for (int o = 16; o > 0; o >>= 1) sq += __shfl_xor_sync(0xffffffffu, sq, o);
        const float m_bf = bfr(mean);
        const float v_bf = bfr(sq * (1.0f / kD));
        const float den = bfr(sqrtf(bfr(v_bf + 1e-5f)));
#pragma unroll
        for (int i = 0; i < 9; i++) {
            int e = 2 * (lane + 32 * i) - kRows1 * r;
            if (e >= 0 && e < kRows1) {
                float a0 = bfr(v[2 * i] - m_bf) / den;
                float a1 = bfr(v[2 * i + 1] - m_bf) / den;
                *reinterpret_cast<uint32_t*>(xn_s + warp * 80 + e) = pack_bf16(a0, a1);
            }
        }
    }
    asm volatile("bar.sync 2, 288;" ::: "memory");
    if (tid == 0) TS(1);

    const int gid = lane >> 2, tig = lane & 3;
    const int lm_i = lane & 7, lm_j = lane >> 3;

    {
        uint32_t bx[9];
#pragma unroll
        for (int ks = 0; ks < 4; ks++) {
            bx[2 * ks] = gid < 4 ? *reinterpret_cast<const uint32_t*>(xn_s + gid * 80 + 16 * ks + 2 * tig) : 0u;
            bx[2 * ks + 1] = gid < 4 ? *reinterpret_cast<const uint32_t*>(xn_s + gid * 80 + 16 * ks + 8 + 2 * tig) : 0u;
        }
        bx[8] = gid < 4 ? *reinterpret_cast<const uint32_t*>(xn_s + gid * 80 + 64 + 2 * tig) : 0u;

        mbar_wait(bar_full + 8 * 0, 0);
        mbar_wait(bar_full + 8 * 1, 0);
        if (tid == 0) TS(2);
        uint32_t* qdst = g_qpart + (size_t)(g * kRanks + r) * kB * kQCols;
#pragma unroll
        for (int t = 0; t < 2; t++) {
            const int m0 = 16 * (warp + 8 * t);
            float c[4] = {0.f, 0.f, 0.f, 0.f};
            const int cgp = (m0 >> 3) + (lm_j & 1);
            const uint32_t bbase = sbase + OFF_A + (cgp >> 3) * BOX_WQ + (((cgp & 7) ^ lm_i) << 4);
            const uint32_t abase = bbase + (lm_i + (lm_j >> 1) * 8) * 128;
#pragma unroll
            for (int ks = 0; ks < 4; ks++) {
                uint32_t a0, a1, a2, a3;
                ldsm_x4_t(abase + ks * 16 * 128, a0, a1, a2, a3);
                mma16816(c, a0, a1, a2, a3, bx[2 * ks], bx[2 * ks + 1]);
            }
            {
                uint32_t a0, a1;
                ldsm_x2_t(bbase + (64 + lm_i) * 128, a0, a1);
                mma1688(c, a0, a1, bx[8]);
            }
            if (tig < 2) {
                const int col = m0 + gid;
                st_word(qdst + (2 * tig) * kQCols + col, tagw(c[0], flag));
                st_word(qdst + (2 * tig + 1) * kQCols + col, tagw(c[1], flag));
                st_word(qdst + (2 * tig) * kQCols + col + 8, tagw(c[2], flag));
                st_word(qdst + (2 * tig + 1) * kQCols + col + 8, tagw(c[3], flag));
            }
        }
        mbar_wait(bar_full + 8 * 2, 0);
        mbar_wait(bar_full + 8 * 3, 0);
        if (tid == 0) TS(3);
        uint32_t* hdst = g_hpart + (size_t)(g * kRanks + r) * kB * kHCols;
        for (int t = warp; t < 18; t += 8) {
            const int m0 = 16 * t;
            float c[4] = {0.f, 0.f, 0.f, 0.f};
            const int cgp = (m0 >> 3) + (lm_j & 1);
            const int bx_ = cgp / 9;
            const uint32_t bbase = sbase + OFF_B + bx_ * BOX_W1 + (cgp - 9 * bx_) * 16;
            const uint32_t abase = bbase + (lm_i + (lm_j >> 1) * 8) * 144;
#pragma unroll
            for (int ks = 0; ks < 4; ks++) {
                uint32_t a0, a1, a2, a3;
                ldsm_x4_t(abase + ks * 16 * 144, a0, a1, a2, a3);
                mma16816(c, a0, a1, a2, a3, bx[2 * ks], bx[2 * ks + 1]);
            }
            {
                uint32_t a0, a1;
                ldsm_x2_t(bbase + (64 + lm_i) * 144, a0, a1);
                mma1688(c, a0, a1, bx[8]);
            }
            if (tig < 2) {
                const int col = m0 + gid;
                st_word(hdst + (2 * tig) * kHCols + col, tagw(c[0], flag));
                st_word(hdst + (2 * tig + 1) * kHCols + col, tagw(c[1], flag));
                st_word(hdst + (2 * tig) * kHCols + col + 8, tagw(c[2], flag));
                st_word(hdst + (2 * tig + 1) * kHCols + col + 8, tagw(c[3], flag));
            }
        }
    }
    __syncwarp();
    if (lane == 0) mbar_arrive(bar_s1);

    {
        const uint32_t* src = g_qpart + (size_t)(g * kRanks) * kB * kQCols + b * kQCols + tid;
        uint32_t w[8];
        for (int it = 0; it < kSpinLimit; it++) {
            uint32_t bad = 0;
#pragma unroll
            for (int p = 0; p < 8; p++) {
                w[p] = ld_word(src + p * kB * kQCols);
                bad |= (w[p] ^ flag);
            }
            if (!(bad & 1u)) break;
        }
        float s = 0.f;
#pragma unroll
        for (int p = 0; p < 8; p++) s += __uint_as_float(w[p]);
        q_s[(tid >> 7) * 136 + (tid & 127)] = __float2bfloat16_rn(s);
    }
    bar_cons();
    if (tid == 0) TS(4);

    const uint32_t slot = sbase + OFF_KV + warp * kSlotBytes;
    float mx, lsum = 0.f;
    uint32_t pb[8];
    {
        uint32_t qa[16];
#pragma unroll
        for (int j = 0; j < 8; j++) {
            qa[2 * j] = gid < 2 ? *reinterpret_cast<const uint32_t*>(q_s + gid * 136 + 16 * j + 2 * tig) : 0u;
            qa[2 * j + 1] = gid < 2 ? *reinterpret_cast<const uint32_t*>(q_s + gid * 136 + 16 * j + 8 + 2 * tig) : 0u;
        }
        mbar_wait(bar_full + 8 * (4 + warp), 0);
        if (tid == 0) TS(5);
        if (tid == 224) TS(7);
        float sc[8][4];
#pragma unroll
        for (int nt = 0; nt < 8; nt++) {
            sc[nt][0] = sc[nt][1] = sc[nt][2] = sc[nt][3] = 0.f;
#pragma unroll
            for (int kk = 0; kk < 4; kk++) {
                const int cg = 4 * kk + lm_j;
                const uint32_t addr =
                    slot + (cg >> 3) * 8192 + (8 * nt + lm_i) * 128 + (((cg & 7) ^ lm_i) << 4);
                uint32_t b0, b1, b2, b3;
                ldsm_x4(addr, b0, b1, b2, b3);
                mma16816(sc[nt], qa[4 * kk], 0u, qa[4 * kk + 1], 0u, b0, b1);
                mma16816(sc[nt], qa[4 * kk + 2], 0u, qa[4 * kk + 3], 0u, b2, b3);
            }
        }
        mx = -INFINITY;
        const float scale = 0.08838834764831845f;
#pragma unroll
        for (int nt = 0; nt < 8; nt++) {
            sc[nt][0] = bfr(bfr(sc[nt][0]) * scale);
            sc[nt][1] = bfr(bfr(sc[nt][1]) * scale);
            mx = fmaxf(mx, fmaxf(sc[nt][0], sc[nt][1]));
        }
        __syncwarp();
        if (lane == 0) mbar_arrive(bar_empty + 8 * warp);
        mx = fmaxf(mx, __shfl_xor_sync(0xffffffffu, mx, 1));
        mx = fmaxf(mx, __shfl_xor_sync(0xffffffffu, mx, 2));
        const float l2e = 1.4426950408889634f;
#pragma unroll
        for (int nt = 0; nt < 8; nt++) {
            float p0 = exp2f((sc[nt][0] - mx) * l2e);
            float p1 = exp2f((sc[nt][1] - mx) * l2e);
            lsum += p0 + p1;
            pb[nt] = pack_bf16(p0, p1);
        }
        lsum += __shfl_xor_sync(0xffffffffu, lsum, 1);
        lsum += __shfl_xor_sync(0xffffffffu, lsum, 2);
    }

    {
        for (int idx = tid; idx < kB * kHCols / 4; idx += 256) {
            const uint32_t* src = g_hpart + (size_t)(g * kRanks) * kB * kHCols + 4 * idx;
            uint4 w[8];
            for (int it = 0; it < kSpinLimit; it++) {
                uint32_t bad = 0;
#pragma unroll
                for (int p = 0; p < 8; p++) {
                    w[p] = ld_word4(src + p * kB * kHCols);
                    bad |= (w[p].x ^ flag) | (w[p].y ^ flag) | (w[p].z ^ flag) | (w[p].w ^ flag);
                }
                if (!(bad & 1u)) break;
            }
            float s0 = 0.f, s1 = 0.f, s2 = 0.f, s3 = 0.f;
#pragma unroll
            for (int p = 0; p < 8; p++) {
                s0 += __uint_as_float(w[p].x);
                s1 += __uint_as_float(w[p].y);
                s2 += __uint_as_float(w[p].z);
                s3 += __uint_as_float(w[p].w);
            }
            const int bb = idx / 72, c4 = idx - bb * 72;
            uint2 pk;
            pk.x = pack_bf16(silu_f(bfr(s0)), silu_f(bfr(s1)));
            pk.y = pack_bf16(silu_f(bfr(s2)), silu_f(bfr(s3)));
            *reinterpret_cast<uint2*>(h_s + bb * 296 + 4 * c4) = pk;
        }
        if (tid == 0) TS(10);
    }

    {
        mbar_wait(bar_full + 8 * (12 + warp), 0);
        if (tid == 0) TS(6);
        if (tid == 224) TS(8);
#pragma unroll
        for (int mt = 0; mt < 8; mt++) {
            float oc[4] = {0.f, 0.f, 0.f, 0.f};
            const int cg = 2 * mt + (lm_j & 1);
#pragma unroll
            for (int ks = 0; ks < 4; ks++) {
                const int key = 16 * ks + (lm_j >> 1) * 8 + lm_i;
                const uint32_t addr = slot + (cg >> 3) * 8192 + key * 128 + (((cg & 7) ^ lm_i) << 4);
                uint32_t a0, a1, a2, a3;
                ldsm_x4_t(addr, a0, a1, a2, a3);
                mma16816(oc, a0, a1, a2, a3, pb[2 * ks], pb[2 * ks + 1]);
            }
            if (tig == 0) {
                const int d = 16 * mt + gid;
                ow_s[warp * 256 + d] = oc[0];
                ow_s[warp * 256 + 128 + d] = oc[1];
                ow_s[warp * 256 + d + 8] = oc[2];
                ow_s[warp * 256 + 128 + d + 8] = oc[3];
            }
        }
        if (lane == 0 || lane == 4) {
            ml_s[warp * 4 + (lane >> 2) * 2] = mx;
            ml_s[warp * 4 + (lane >> 2) * 2 + 1] = lsum;
        }
    }
    bar_cons();
    if (tid == 0) TS(13);

    {
        const int head = tid >> 7;
        float M = -INFINITY;
#pragma unroll
        for (int w = 0; w < 8; w++) M = fmaxf(M, ml_s[w * 4 + head * 2]);
        float L = 0.f, O = 0.f;
#pragma unroll
        for (int w = 0; w < 8; w++) {
            const float wgt = exp2f((ml_s[w * 4 + head * 2] - M) * 1.4426950408889634f);
            L += wgt * ml_s[w * 4 + head * 2 + 1];
            O += wgt * ow_s[w * 256 + tid];
        }
        uint32_t* od = g_opart + (size_t)((g * kB + b) * 2 + half) * 272 + head * 136;
        st_word(od + (tid & 127), tagw(O, flag));
        if ((tid & 127) == 0) st_word2(od + 128, tagw(M, flag), tagw(L, flag));

        mbar_wait(bar_full + 8 * 20, 0);
        mbar_wait(bar_full + 8 * 21, 0);
        if (tid == 0) TS(11);
        for (int nt = 7 - warp; nt < 9; nt += 8) {
            float c[4];
            gemv3_tile<18, 296>(sbase + OFF_B, h_s, nt, lane, c);
            if (gid < 4)
                st_word2(g_fpart + (size_t)(((r * 9 + nt) * 2 + 1) * kGroups + g) * 32 + gid * 8 + 2 * tig,
                         tagw(c[0], flag), tagw(c[1], flag));
        }
        if (tid == 0) TS(12);

        const uint32_t* src = g_opart + (size_t)(g * kB * 2) * 272 + head * 136;
        uint32_t wv[8];
        uint2 wml[8];
        for (int it = 0; it < kSpinLimit; it++) {
            uint32_t bad = 0;
#pragma unroll
            for (int p = 0; p < 8; p++) {
                wv[p] = ld_word(src + p * 272 + (tid & 127));
                wml[p] = ld_word2(src + p * 272 + 128);
                bad |= (wv[p] ^ flag) | (wml[p].x ^ flag) | (wml[p].y ^ flag);
            }
            if (!(bad & 1u)) break;
        }
#pragma unroll
        for (int bb = 0; bb < 4; bb++) {
            const float m0 = __uint_as_float(wml[2 * bb].x), m1 = __uint_as_float(wml[2 * bb + 1].x);
            const float MM = fmaxf(m0, m1);
            const float e0 = exp2f((m0 - MM) * 1.4426950408889634f), e1 = exp2f((m1 - MM) * 1.4426950408889634f);
            const float LL = e0 * __uint_as_float(wml[2 * bb].y) + e1 * __uint_as_float(wml[2 * bb + 1].y);
            const float OO = e0 * __uint_as_float(wv[2 * bb]) + e1 * __uint_as_float(wv[2 * bb + 1]);
            o_s[bb * 264 + tid] = __float2bfloat16_rn(OO / LL);
        }
    }
    bar_cons();
    if (tid == 0) TS(9);

    {
        mbar_wait(bar_full + 8 * 22, 0);
        mbar_wait(bar_full + 8 * 23, 0);
        if (tid == 0) TS(14);
        for (int nt = warp; nt < 9; nt += 8) {
            float c[4];
            gemv3_tile<16, 264>(sbase + OFF_A, o_s, nt, lane, c);
            if (gid < 4)
                st_word2(g_fpart + (size_t)(((r * 9 + nt) * 2 + 0) * kGroups + g) * 32 + gid * 8 + 2 * tig,
                         tagw(c[0], flag), tagw(c[1], flag));
        }
    }
    if (tid == 0) TS(15);

    if (cta < kFinalCons) {
        float4* red = reinterpret_cast<float4*>(sgen + OFF_RED);
        {
            const uint32_t* src = g_fpart + (size_t)cta * 1024 + 4 * tid;
            uint4 w;
            for (int it = 0; it < kSpinLimit; it++) {
                w = ld_word4(src);
                const uint32_t bad = (w.x ^ flag) | (w.y ^ flag) | (w.z ^ flag) | (w.w ^ flag);
                if (!(bad & 1u)) break;
            }
            float4 s = make_float4(__uint_as_float(w.x), __uint_as_float(w.y), __uint_as_float(w.z),
                                   __uint_as_float(w.w));
#pragma unroll
            for (int o = 8; o <= 16; o <<= 1) {
                s.x += __shfl_xor_sync(0xffffffffu, s.x, o);
                s.y += __shfl_xor_sync(0xffffffffu, s.y, o);
                s.z += __shfl_xor_sync(0xffffffffu, s.z, o);
                s.w += __shfl_xor_sync(0xffffffffu, s.w, o);
            }
            if (lane < 8) red[warp * 8 + lane] = s;
        }
        bar_cons();
        if (tid == 0) TS(16);
        if (tid < 32) {
            const float* rf = reinterpret_cast<const float*>(red);
            float sv = 0.f, gv = 0.f;
#pragma unroll
            for (int w = 0; w < 4; w++) {
                sv += rf[w * 32 + tid];
                gv += rf[(4 + w) * 32 + tid];
            }
            const int rc = cta / 9, ntc = cta - 9 * rc;
            const float gg = bfr(silu_f(bfr(gv)));
            const float sg = bfr(bfr(sv) * gg);
            out[(tid >> 3) * kD + kCols3 * rc + 8 * ntc + (tid & 7)] = __float2bfloat16_rn(x_fin + sg);
        }
        if (tid == 0) TS(17);
        if (cta == 0 && tid == 0) {
            asm volatile("st.relaxed.gpu.global.u32 [%0], %1;" ::"l"(&g_epoch), "r"(epoch + 1u) : "memory");
        }
    }
}

typedef CUresult (*PFN_encodeTiled)(CUtensorMap*, CUtensorMapDataType, cuuint32_t, void*, const cuuint64_t*,
                                    const cuuint64_t*, const cuuint32_t*, const cuuint32_t*, CUtensorMapInterleave,
                                    CUtensorMapSwizzle, CUtensorMapL2promotion, CUtensorMapFloatOOBfill);

void make_map(PFN_encodeTiled enc, CUtensorMap* map, const void* ptr, uint64_t cols, uint64_t rows, uint32_t box_c,
              uint32_t box_r, CUtensorMapSwizzle swz, CUtensorMapL2promotion promo) {
    cuuint64_t gdim[2] = {cols, rows};
    cuuint64_t gstr[1] = {cols * 2};
    cuuint32_t box[2] = {box_c, box_r};
    cuuint32_t estr[2] = {1, 1};
    enc(map, CU_TENSOR_MAP_DATA_TYPE_BFLOAT16, 2, const_cast<void*>(ptr), gdim, gstr, box, estr,
        CU_TENSOR_MAP_INTERLEAVE_NONE, swz, promo, CU_TENSOR_MAP_FLOAT_OOB_FILL_NONE);
}

}

extern "C" void kernel_launch(void* const* d_in, const int* in_sizes, int n_in, void* d_out, int out_size) {
    (void)in_sizes;
    (void)n_in;
    (void)out_size;
    static PFN_encodeTiled enc = nullptr;
    if (!enc) {
        void* fn = nullptr;
        cudaDriverEntryPointQueryResult st;
        cudaGetDriverEntryPoint("cuTensorMapEncodeTiled", &fn, cudaEnableDefault, &st);
        enc = (PFN_encodeTiled)fn;
        cudaFuncSetAttribute(fused_decode_kernel, cudaFuncAttributeMaxDynamicSharedMemorySize, SMEM_BYTES);
    }
    CUtensorMap kmap, vmap, womap, w2map, wqmap, w1map;
    make_map(enc, &wqmap, d_in[3], kNQ, kD, 64, kRows1, CU_TENSOR_MAP_SWIZZLE_128B, CU_TENSOR_MAP_L2_PROMOTION_L2_256B);
    make_map(enc, &w1map, d_in[6], kF, kD, 72, kRows1, CU_TENSOR_MAP_SWIZZLE_NONE, CU_TENSOR_MAP_L2_PROMOTION_L2_256B);
    make_map(enc, &kmap, d_in[1], kDh, (uint64_t)kB * kHkv * kSk, 64, kChunkKeys, CU_TENSOR_MAP_SWIZZLE_128B,
             CU_TENSOR_MAP_L2_PROMOTION_L2_256B);
    make_map(enc, &vmap, d_in[2], kDh, (uint64_t)kB * kHkv * kSk, 64, kChunkKeys, CU_TENSOR_MAP_SWIZZLE_128B,
             CU_TENSOR_MAP_L2_PROMOTION_L2_256B);
    make_map(enc, &womap, d_in[4], kD, kNQ, kCols3, 128, CU_TENSOR_MAP_SWIZZLE_NONE,
             CU_TENSOR_MAP_L2_PROMOTION_L2_128B);
    make_map(enc, &w2map, d_in[7], kD, kF, kCols3, 144, CU_TENSOR_MAP_SWIZZLE_NONE,
             CU_TENSOR_MAP_L2_PROMOTION_L2_128B);
    fused_decode_kernel<<<kCTAs, 288, SMEM_BYTES>>>(kmap, vmap, womap, w2map, wqmap, w1map,
                                                    (const __nv_bfloat16*)d_in[0], (__nv_bfloat16*)d_out);
}
```

```cpp
#include <cuda_runtime.h>
#include <cuda_bf16.h>
#include <cuda.h>
#include <stdint.h>

namespace {

constexpr int kB = 4, kD = 576, kHkv = 16, kSk = 4096, kDh = 128, kWin = 1024, kF = 4608;
constexpr int kNQ = 4096;
constexpr int kGroups = 16, kRanks = 8, kCTAs = 128;
constexpr int kRows1 = 72;
constexpr int kQCols = 256, kHCols = 288;
constexpr int kCols3 = 72;
constexpr int kChunkKeys = 64;
constexpr int kFinalCons = 72;

constexpr int kSlotBytes = 16384;
constexpr int OFF_KV = 0;
constexpr int STR_W3 = 144;
constexpr int BOX_WQ = kRows1 * 128;
constexpr int BOX_W1 = kRows1 * 144;
constexpr int OFF_A = 8 * kSlotBytes;
constexpr int SZ_A = 4 * BOX_WQ;
constexpr int OFF_B = OFF_A + SZ_A;
constexpr int SZ_B = 4 * BOX_W1;
constexpr int OFF_XN = OFF_B + SZ_B;
constexpr int OFF_Q = OFF_XN + 640;
constexpr int OFF_H = OFF_Q + 544;
constexpr int OFF_O = OFF_H + 4 * 296 * 2;
constexpr int OFF_P = OFF_O + 4 * 264 * 2;
constexpr int OFF_ML = OFF_P + 2 * 520 * 2;
constexpr int OFF_BAR = OFF_ML + 128;
constexpr int SMEM_USED = OFF_BAR + 288;
constexpr int SMEM_BYTES = SMEM_USED + 1024;

static_assert(OFF_A % 128 == 0 && OFF_B % 128 == 0, "align");
static_assert(OFF_BAR % 8 == 0, "align");
static_assert(SMEM_BYTES <= 232448, "smem");

__device__ __align__(128) uint32_t g_qpart[kGroups * kRanks * kB * kQCols];
__device__ __align__(128) uint32_t g_hpart[kGroups * kRanks * kB * kHCols];
__device__ __align__(128) uint32_t g_opart[kGroups * kB * 2 * 2 * 136];
__device__ __align__(128) uint32_t g_fpart[kFinalCons * 2 * kGroups * 32];
__device__ uint32_t g_epoch;

constexpr int kSpinLimit = 1 << 22;
#define KWINDOW 4
constexpr int kWindow = KWINDOW;

#define ORDER 1
__constant__ int c_order[24] = {0, 1, 2, 3, 4, 5, 6, 7, 8, 9, 10, 11, 20, 21, 22, 23, 12, 13, 14, 15, 16, 17, 18, 19};

#define TS(k)
#define TS2(k)

__device__ __forceinline__ uint32_t smem_u32(const void* p) {
    return (uint32_t)__cvta_generic_to_shared(p);
}
__device__ __forceinline__ void mbar_init(uint32_t bar, uint32_t count) {
    asm volatile("mbarrier.init.shared::cta.b64 [%0], %1;" ::"r"(bar), "r"(count) : "memory");
}
__device__ __forceinline__ void mbar_expect_tx(uint32_t bar, uint32_t bytes) {
    asm volatile("mbarrier.arrive.expect_tx.shared::cta.b64 _, [%0], %1;" ::"r"(bar), "r"(bytes) : "memory");
}
__device__ __forceinline__ void mbar_arrive(uint32_t bar) {
    asm volatile("mbarrier.arrive.shared::cta.b64 _, [%0];" ::"r"(bar) : "memory");
}
__device__ __forceinline__ bool mbar_try_wait(uint32_t bar, uint32_t parity) {
    uint32_t ok;
    asm volatile(
        "{\n .reg .pred p;\n mbarrier.try_wait.parity.shared::cta.b64 p, [%1], %2;\n selp.u32 %0, 1, 0, p;\n}"
        : "=r"(ok)
        : "r"(bar), "r"(parity)
        : "memory");
    return ok != 0;
}
__device__ __forceinline__ void mbar_wait(uint32_t bar, uint32_t parity) {
    for (int i = 0; i < kSpinLimit; i++) {
        if (mbar_try_wait(bar, parity)) break;
    }
}
__device__ __forceinline__ void bulk_g2s(uint32_t dst, const void* src, uint32_t bytes, uint32_t bar) {
    asm volatile(
        "cp.async.bulk.shared::cluster.global.mbarrier::complete_tx::bytes [%0], [%1], %2, [%3];" ::"r"(dst),
        "l"(src), "r"(bytes), "r"(bar)
        : "memory");
}
__device__ __forceinline__ void tma_2d(uint32_t dst, const CUtensorMap* map, int c0, int c1, uint32_t bar) {
    asm volatile(
        "cp.async.bulk.tensor.2d.shared::cluster.global.mbarrier::complete_tx::bytes [%0], [%1, {%3, %4}], [%2];" ::"r"(dst),
        "l"(map), "r"(bar), "r"(c0), "r"(c1)
        : "memory");
}
__device__ __forceinline__ void ldsm_x4(uint32_t addr, uint32_t& r0, uint32_t& r1, uint32_t& r2, uint32_t& r3) {
    asm volatile("ldmatrix.sync.aligned.m8n8.x4.shared.b16 {%0,%1,%2,%3}, [%4];"
                 : "=r"(r0), "=r"(r1), "=r"(r2), "=r"(r3)
                 : "r"(addr)
                 : "memory");
}
__device__ __forceinline__ void ldsm_x4_t(uint32_t addr, uint32_t& r0, uint32_t& r1, uint32_t& r2, uint32_t& r3) {
    asm volatile("ldmatrix.sync.aligned.m8n8.x4.trans.shared.b16 {%0,%1,%2,%3}, [%4];"
                 : "=r"(r0), "=r"(r1), "=r"(r2), "=r"(r3)
                 : "r"(addr)
                 : "memory");
}
__device__ __forceinline__ void ldsm_x2_t(uint32_t addr, uint32_t& r0, uint32_t& r1) {
    asm volatile("ldmatrix.sync.aligned.m8n8.x2.trans.shared.b16 {%0,%1}, [%2];"
                 : "=r"(r0), "=r"(r1)
                 : "r"(addr)
                 : "memory");
}
__device__ __forceinline__ void mma16816(float (&c)[4], uint32_t a0, uint32_t a1, uint32_t a2, uint32_t a3,
                                         uint32_t b0, uint32_t b1) {
    asm volatile(
        "mma.sync.aligned.m16n8k16.row.col.f32.bf16.bf16.f32 {%0,%1,%2,%3}, {%4,%5,%6,%7}, {%8,%9}, {%0,%1,%2,%3};"
        : "+f"(c[0]), "+f"(c[1]), "+f"(c[2]), "+f"(c[3])
        : "r"(a0), "r"(a1), "r"(a2), "r"(a3), "r"(b0), "r"(b1));
}
__device__ __forceinline__ void mma1688(float (&c)[4], uint32_t a0, uint32_t a1, uint32_t b0) {
    asm volatile("mma.sync.aligned.m16n8k8.row.col.f32.bf16.bf16.f32 {%0,%1,%2,%3}, {%4,%5}, {%6}, {%0,%1,%2,%3};"
                 : "+f"(c[0]), "+f"(c[1]), "+f"(c[2]), "+f"(c[3])
                 : "r"(a0), "r"(a1), "r"(b0));
}
__device__ __forceinline__ void bar_cons() { asm volatile("bar.sync 1, 256;" ::: "memory"); }

__device__ __forceinline__ float bfr(float x) { return __bfloat162float(__float2bfloat16_rn(x)); }
__device__ __forceinline__ uint32_t pack_bf16(float lo, float hi) {
    __nv_bfloat162 v = __floats2bfloat162_rn(lo, hi);
    return *reinterpret_cast<uint32_t*>(&v);
}
__device__ __forceinline__ uint32_t tagw(float v, uint32_t flag) { return (__float_as_uint(v) & ~1u) | flag; }
__device__ __forceinline__ void st_word(uint32_t* p, uint32_t v) {
    asm volatile("st.relaxed.gpu.global.u32 [%0], %1;" ::"l"(p), "r"(v) : "memory");
}
__device__ __forceinline__ void st_word2(uint32_t* p, uint32_t v0, uint32_t v1) {
    asm volatile("st.relaxed.gpu.global.v2.u32 [%0], {%1,%2};" ::"l"(p), "r"(v0), "r"(v1) : "memory");
}
__device__ __forceinline__ void st_word4(uint32_t* p, uint32_t v) {
    asm volatile("st.relaxed.gpu.global.v4.u32 [%0], {%1,%1,%1,%1};" ::"l"(p), "r"(v) : "memory");
}
__device__ __forceinline__ uint32_t ld_word(const uint32_t* p) {
    uint32_t v;
    asm volatile("ld.relaxed.gpu.global.u32 %0, [%1];" : "=r"(v) : "l"(p) : "memory");
    return v;
}
__device__ __forceinline__ uint2 ld_word2(const uint32_t* p) {
    uint2 v;
    asm volatile("ld.relaxed.gpu.global.v2.u32 {%0,%1}, [%2];" : "=r"(v.x), "=r"(v.y) : "l"(p) : "memory");
    return v;
}
__device__ __forceinline__ uint4 ld_word4(const uint32_t* p) {
    uint4 v;
    asm volatile("ld.relaxed.gpu.global.v4.u32 {%0,%1,%2,%3}, [%4];"
                 : "=r"(v.x), "=r"(v.y), "=r"(v.z), "=r"(v.w)
                 : "l"(p)
                 : "memory");
    return v;
}
__device__ __forceinline__ float silu_f(float x) { return x / (1.0f + __expf(-x)); }

template <int KSTEPS, int ASTRIDE>
__device__ __forceinline__ void gemv3_tile(uint32_t wbuf, const __nv_bfloat16* act, int nt, int lane, float (&c)[4]) {
    const int gid = lane >> 2, tig = lane & 3, lm_i = lane & 7, lm_j = lane >> 3;
    const uint32_t wb = wbuf + (8 * lm_j + lm_i) * STR_W3 + nt * 16;
    const __nv_bfloat16* ap = act + (gid & 3) * ASTRIDE + 2 * tig;
    float acc[4][4];
#pragma unroll
    for (int i = 0; i < 4; i++) acc[i][0] = acc[i][1] = acc[i][2] = acc[i][3] = 0.f;
#pragma unroll
    for (int kk = 0; kk < KSTEPS / 2; kk++) {
        uint32_t b0, b1, b2, b3;
        ldsm_x4_t(wb + kk * 32 * STR_W3, b0, b1, b2, b3);
        uint32_t a0 = *reinterpret_cast<const uint32_t*>(ap + 32 * kk);
        uint32_t a2 = *reinterpret_cast<const uint32_t*>(ap + 32 * kk + 8);
        uint32_t a4 = *reinterpret_cast<const uint32_t*>(ap + 32 * kk + 16);
        uint32_t a6 = *reinterpret_cast<const uint32_t*>(ap + 32 * kk + 24);
        if (gid >= 4) a0 = a2 = a4 = a6 = 0u;
        mma16816(acc[(2 * kk) & 3], a0, 0u, a2, 0u, b0, b1);
        mma16816(acc[(2 * kk + 1) & 3], a4, 0u, a6, 0u, b2, b3);
    }
    c[0] = (acc[0][0] + acc[1][0]) + (acc[2][0] + acc[3][0]);
    c[1] = (acc[0][1] + acc[1][1]) + (acc[2][1] + acc[3][1]);
    c[2] = c[3] = 0.f;
}

__global__ void __launch_bounds__(288, 1)
fused_decode_kernel(const __grid_constant__ CUtensorMap kmap, const __grid_constant__ CUtensorMap vmap,
                    const __grid_constant__ CUtensorMap womap, const __grid_constant__ CUtensorMap w2map,
                    const __grid_constant__ CUtensorMap wqmap, const __grid_constant__ CUtensorMap w1map,
                    const __nv_bfloat16* __restrict__ x, __nv_bfloat16* __restrict__ out) {
    extern __shared__ uint8_t smem_raw[];
    const uint32_t raw_u32 = smem_u32(smem_raw);
    const uint32_t sbase = (raw_u32 + 1023u) & ~1023u;
    uint8_t* sgen = smem_raw + (sbase - raw_u32);

    const int tid = threadIdx.x, warp = tid >> 5, lane = tid & 31;
    const int cta = blockIdx.x;
    const int g = cta >> 3, r = cta & 7;
    const int b = r >> 1, half = r & 1;

    const uint32_t bar_full = sbase + OFF_BAR;
    const uint32_t bar_empty = sbase + OFF_BAR + 24 * 8;
    const uint32_t bar_s1 = sbase + OFF_BAR + 32 * 8;

    const int kv_row0 = (b * kHkv + g) * kSk + (kSk - kWin) + half * 512;

    if (warp == 8) {
        if (lane == 0) {
            TS(0);
            for (int i = 0; i < 32; i++) mbar_init(bar_full + 8 * i, 1);
            mbar_init(bar_s1, 8);
            asm volatile("fence.mbarrier_init.release.cluster;" ::: "memory");
            asm volatile("fence.proxy.async.shared::cta;" ::: "memory");
        }
        __syncwarp();
        asm volatile("bar.arrive 2, 288;" ::: "memory");
#pragma unroll 1
        for (int n = 0; n < 24; n++) {
            const int u = c_order[n];
            if (n >= kWindow) mbar_wait(bar_full + 8 * c_order[n - kWindow], 0);
            const uint32_t bar = bar_full + 8 * u;
            if (u < 2) {
                if (lane == 0) {
                    mbar_expect_tx(bar, 2 * BOX_WQ);
                    tma_2d(sbase + OFF_A + (2 * u) * BOX_WQ, &wqmap, kQCols * g + 128 * u, kRows1 * r, bar);
                    tma_2d(sbase + OFF_A + (2 * u + 1) * BOX_WQ, &wqmap, kQCols * g + 128 * u + 64, kRows1 * r, bar);
                }
            } else if (u < 4) {
                if (lane == 0) {
                    mbar_expect_tx(bar, 2 * BOX_W1);
                    tma_2d(sbase + OFF_B + (2 * u - 4) * BOX_W1, &w1map, kHCols * g + 144 * (u - 2), kRows1 * r, bar);
                    tma_2d(sbase + OFF_B + (2 * u - 3) * BOX_W1, &w1map, kHCols * g + 144 * (u - 2) + 72, kRows1 * r, bar);
                }
            } else if (u < 20) {
                const int c = (u - 4) & 7;
                if (u >= 12) mbar_wait(bar_empty + 8 * c, 0);
                if (lane == 0) {
                    const CUtensorMap* mp = u >= 12 ? &vmap : &kmap;
                    mbar_expect_tx(bar, kSlotBytes);
                    tma_2d(sbase + OFF_KV + c * kSlotBytes, mp, 0, kv_row0 + kChunkKeys * c, bar);
                    tma_2d(sbase + OFF_KV + c * kSlotBytes + 8192, mp, 64, kv_row0 + kChunkKeys * c, bar);
                }
            } else if (u < 22) {
                mbar_wait(bar_s1, 0);
                if (lane == 0) {
                    mbar_expect_tx(bar, 144 * STR_W3);
                    tma_2d(sbase + OFF_B + (u - 20) * 144 * STR_W3, &w2map, kCols3 * r, kHCols * g + 144 * (u - 20), bar);
                }
            } else {
                mbar_wait(bar_s1, 0);
                if (lane == 0) {
                    mbar_expect_tx(bar, 128 * STR_W3);
                    tma_2d(sbase + OFF_A + (u - 22) * 128 * STR_W3, &womap, kCols3 * r, kQCols * g + 128 * (u - 22), bar);
                }
            }
            if (lane == 0) TS2(n);
            __syncwarp();
        }
        mbar_wait(bar_full + 8 * 22, 0);
        mbar_wait(bar_full + 8 * 23, 0);
        asm volatile("bar.sync 3, 288;" ::: "memory");
        const uint32_t flag_p = *reinterpret_cast<volatile uint32_t*>(sgen + OFF_BAR + 280);
        {
            float c[4];
            gemv3_tile<16, 264>(sbase + OFF_A, reinterpret_cast<const __nv_bfloat16*>(sgen + OFF_O), 8, lane, c);
            if ((lane >> 2) < 4)
                st_word2(g_fpart + (size_t)(((r * 9 + 8) * 2 + 0) * kGroups + g) * 32 + (lane >> 2) * 8 + 2 * (lane & 3),
                         tagw(c[0], flag_p), tagw(c[1], flag_p));
        }
        return;
    }

    uint32_t epoch;
    asm volatile("ld.relaxed.gpu.global.u32 %0, [%1];" : "=r"(epoch) : "l"(&g_epoch) : "memory");
    uint32_t xw[9];
    if (warp < 4) {
        const uint32_t* xr = reinterpret_cast<const uint32_t*>(x + warp * kD);
#pragma unroll
        for (int i = 0; i < 9; i++) xw[i] = __ldg(xr + lane + 32 * i);
    }
    float x_fin[4] = {0.f, 0.f, 0.f, 0.f};
    if (cta < kFinalCons && tid < 8) {
        const int rc = cta / 9, ntc = cta - 9 * rc;
        const uint2 xv = __ldg(reinterpret_cast<const uint2*>(x + (tid >> 1) * kD + kCols3 * rc + 8 * ntc + (tid & 1) * 4));
        x_fin[0] = __uint_as_float(xv.x << 16);
        x_fin[1] = __uint_as_float(xv.x & 0xffff0000u);
        x_fin[2] = __uint_as_float(xv.y << 16);
        x_fin[3] = __uint_as_float(xv.y & 0xffff0000u);
    }
    const uint32_t flag = (epoch + 1u) & 1u;

    __nv_bfloat16* xn_s = reinterpret_cast<__nv_bfloat16*>(sgen + OFF_XN);
    __nv_bfloat16* q_s = reinterpret_cast<__nv_bfloat16*>(sgen + OFF_Q);
    __nv_bfloat16* h_s = reinterpret_cast<__nv_bfloat16*>(sgen + OFF_H);
    __nv_bfloat16* o_s = reinterpret_cast<__nv_bfloat16*>(sgen + OFF_O);
    __nv_bfloat16* p_s = reinterpret_cast<__nv_bfloat16*>(sgen + OFF_P);
    float* ml_s = reinterpret_cast<float*>(sgen + OFF_ML);

    if (tid == 0) *reinterpret_cast<volatile uint32_t*>(sgen + OFF_BAR + 280) = flag;
    {
        const uint32_t inv = flag ^ 1u;
        st_word4(g_qpart + (size_t)(g * kRanks + r) * kB * kQCols + 4 * tid, inv);
        uint32_t* hd = g_hpart + (size_t)(g * kRanks + r) * kB * kHCols;
        for (int i = tid; i < kB * kHCols / 4; i += 256) st_word4(hd + 4 * i, inv);
        if (tid < 68) st_word4(g_opart + (size_t)((g * kB + b) * 2 + half) * 272 + 4 * tid, inv);
        if (tid >= 96 && tid < 96 + 144) {
            const int i = tid - 96;
            const int nt = i >> 4, wh = (i >> 3) & 1, c4 = i & 7;
            st_word4(g_fpart + (size_t)(((r * 9 + nt) * 2 + wh) * kGroups + g) * 32 + 4 * c4, inv);
        }
    }

    if (warp < 4) {
        float v[18];
        float sum = 0.f;
#pragma unroll
        for (int i = 0; i < 9; i++) {
            v[2 * i] = __uint_as_float(xw[i] << 16);
            v[2 * i + 1] = __uint_as_float(xw[i] & 0xffff0000u);
            sum += v[2 * i] + v[2 * i + 1];
        }
#pragma unroll
        for (int o = 16; o > 0; o >>= 1) sum += __shfl_xor_sync(0xffffffffu, sum, o);
        const float mean = sum * (1.0f / kD);
        float sq = 0.f;
#pragma unroll
        for (int i = 0; i < 18; i++) {
            float d = v[i] - mean;
            sq += d * d;
        }
#pragma unroll
        for (int o = 16; o > 0; o >>= 1) sq += __shfl_xor_sync(0xffffffffu, sq, o);
        const float m_bf = bfr(mean);
        const float v_bf = bfr(sq * (1.0f / kD));
        const float den = bfr(sqrtf(bfr(v_bf + 1e-5f)));
#pragma unroll
        for (int i = 0; i < 9; i++) {
            int e = 2 * (lane + 32 * i) - kRows1 * r;
            if (e >= 0 && e < kRows1) {
                float a0 = bfr(v[2 * i] - m_bf) / den;
                float a1 = bfr(v[2 * i + 1] - m_bf) / den;
                *reinterpret_cast<uint32_t*>(xn_s + warp * 80 + e) = pack_bf16(a0, a1);
            }
        }
    }
    asm volatile("bar.sync 2, 288;" ::: "memory");
    if (tid == 0) TS(1);

    const int gid = lane >> 2, tig = lane & 3;
    const int lm_i = lane & 7, lm_j = lane >> 3;

    {
        uint32_t bx[9];
#pragma unroll
        for (int ks = 0; ks < 4; ks++) {
            bx[2 * ks] = gid < 4 ? *reinterpret_cast<const uint32_t*>(xn_s + gid * 80 + 16 * ks + 2 * tig) : 0u;
            bx[2 * ks + 1] = gid < 4 ? *reinterpret_cast<const uint32_t*>(xn_s + gid * 80 + 16 * ks + 8 + 2 * tig) : 0u;
        }
        bx[8] = gid < 4 ? *reinterpret_cast<const uint32_t*>(xn_s + gid * 80 + 64 + 2 * tig) : 0u;

        mbar_wait(bar_full + 8 * 0, 0);
        mbar_wait(bar_full + 8 * 1, 0);
        if (tid == 0) TS(2);
        uint32_t* qdst = g_qpart + (size_t)(g * kRanks + r) * kB * kQCols;
#pragma unroll
        for (int t = 0; t < 2; t++) {
            const int m0 = 16 * (warp + 8 * t);
            float c[4] = {0.f, 0.f, 0.f, 0.f};
            const int cgp = (m0 >> 3) + (lm_j & 1);
            const uint32_t bbase = sbase + OFF_A + (cgp >> 3) * BOX_WQ + (((cgp & 7) ^ lm_i) << 4);
            const uint32_t abase = bbase + (lm_i + (lm_j >> 1) * 8) * 128;
#pragma unroll
            for (int ks = 0; ks < 4; ks++) {
                uint32_t a0, a1, a2, a3;
                ldsm_x4_t(abase + ks * 16 * 128, a0, a1, a2, a3);
                mma16816(c, a0, a1, a2, a3, bx[2 * ks], bx[2 * ks + 1]);
            }
            {
                uint32_t a0, a1;
                ldsm_x2_t(bbase + (64 + lm_i) * 128, a0, a1);
                mma1688(c, a0, a1, bx[8]);
            }
            if (tig < 2) {
                const int col = m0 + gid;
                st_word(qdst + (2 * tig) * kQCols + col, tagw(c[0], flag));
                st_word(qdst + (2 * tig + 1) * kQCols + col, tagw(c[1], flag));
                st_word(qdst + (2 * tig) * kQCols + col + 8, tagw(c[2], flag));
                st_word(qdst + (2 * tig + 1) * kQCols + col + 8, tagw(c[3], flag));
            }
        }
        mbar_wait(bar_full + 8 * 2, 0);
        mbar_wait(bar_full + 8 * 3, 0);
        if (tid == 0) TS(3);
        uint32_t* hdst = g_hpart + (size_t)(g * kRanks + r) * kB * kHCols;
        for (int t = warp; t < 18; t += 8) {
            const int m0 = 16 * t;
            float c[4] = {0.f, 0.f, 0.f, 0.f};
            const int cgp = (m0 >> 3) + (lm_j & 1);
            const int bx_ = cgp / 9;
            const uint32_t bbase = sbase + OFF_B + bx_ * BOX_W1 + (cgp - 9 * bx_) * 16;
            const uint32_t abase = bbase + (lm_i + (lm_j >> 1) * 8) * 144;
#pragma unroll
            for (int ks = 0; ks < 4; ks++) {
                uint32_t a0, a1, a2, a3;
                ldsm_x4_t(abase + ks * 16 * 144, a0, a1, a2, a3);
                mma16816(c, a0, a1, a2, a3, bx[2 * ks], bx[2 * ks + 1]);
            }
            {
                uint32_t a0, a1;
                ldsm_x2_t(bbase + (64 + lm_i) * 144, a0, a1);
                mma1688(c, a0, a1, bx[8]);
            }
            if (tig < 2) {
                const int col = m0 + gid;
                st_word(hdst + (2 * tig) * kHCols + col, tagw(c[0], flag));
                st_word(hdst + (2 * tig + 1) * kHCols + col, tagw(c[1], flag));
                st_word(hdst + (2 * tig) * kHCols + col + 8, tagw(c[2], flag));
                st_word(hdst + (2 * tig + 1) * kHCols + col + 8, tagw(c[3], flag));
            }
        }
    }
    __syncwarp();
    if (lane == 0) mbar_arrive(bar_s1);

    {
        const uint32_t* src = g_qpart + (size_t)(g * kRanks) * kB * kQCols + b * kQCols + tid;
        uint32_t w[8];
        for (int it = 0; it < kSpinLimit; it++) {
            uint32_t bad = 0;
#pragma unroll
            for (int p = 0; p < 8; p++) {
                w[p] = ld_word(src + p * kB * kQCols);
                bad |= (w[p] ^ flag);
            }
            if (!(bad & 1u)) break;
        }
        float s = 0.f;
#pragma unroll
        for (int p = 0; p < 8; p++) s += __uint_as_float(w[p]);
        q_s[(tid >> 7) * 136 + (tid & 127)] = __float2bfloat16_rn(s);
    }
    bar_cons();
    if (tid == 0) TS(4);

    float sc[8][2];
    {
        const uint32_t slot = sbase + OFF_KV + warp * kSlotBytes;
        uint32_t qa[16];
#pragma unroll
        for (int j = 0; j < 8; j++) {
            qa[2 * j] = gid < 2 ? *reinterpret_cast<const uint32_t*>(q_s + gid * 136 + 16 * j + 2 * tig) : 0u;
            qa[2 * j + 1] = gid < 2 ? *reinterpret_cast<const uint32_t*>(q_s + gid * 136 + 16 * j + 8 + 2 * tig) : 0u;
        }
        mbar_wait(bar_full + 8 * (4 + warp), 0);
        if (tid == 0) TS(5);
        if (tid == 224) TS(7);
        float mx = -INFINITY;
        const float scale = 0.08838834764831845f;
#pragma unroll
        for (int nt = 0; nt < 8; nt++) {
            float acc[4] = {0.f, 0.f, 0.f, 0.f};
#pragma unroll
            for (int kk = 0; kk < 4; kk++) {
                const int cg = 4 * kk + lm_j;
                const uint32_t addr =
                    slot + (cg >> 3) * 8192 + (8 * nt + lm_i) * 128 + (((cg & 7) ^ lm_i) << 4);
                uint32_t b0, b1, b2, b3;
                ldsm_x4(addr, b0, b1, b2, b3);
                mma16816(acc, qa[4 * kk], 0u, qa[4 * kk + 1], 0u, b0, b1);
                mma16816(acc, qa[4 * kk + 2], 0u, qa[4 * kk + 3], 0u, b2, b3);
            }
            sc[nt][0] = bfr(bfr(acc[0]) * scale);
            sc[nt][1] = bfr(bfr(acc[1]) * scale);
            mx = fmaxf(mx, fmaxf(sc[nt][0], sc[nt][1]));
        }
        __syncwarp();
        if (lane == 0) mbar_arrive(bar_empty + 8 * warp);
        mx = fmaxf(mx, __shfl_xor_sync(0xffffffffu, mx, 1));
        mx = fmaxf(mx, __shfl_xor_sync(0xffffffffu, mx, 2));
        if (lane == 0 || lane == 4) ml_s[(lane >> 2) * 8 + warp] = mx;
    }

    {
        for (int idx = tid; idx < kB * kHCols / 4; idx += 256) {
            const uint32_t* src = g_hpart + (size_t)(g * kRanks) * kB * kHCols + 4 * idx;
            uint4 w[8];
            for (int it = 0; it < kSpinLimit; it++) {
                uint32_t bad = 0;
#pragma unroll
                for (int p = 0; p < 8; p++) {
                    w[p] = ld_word4(src + p * kB * kHCols);
                    bad |= (w[p].x ^ flag) | (w[p].y ^ flag) | (w[p].z ^ flag) | (w[p].w ^ flag);
                }
                if (!(bad & 1u)) break;
            }
            float s0 = 0.f, s1 = 0.f, s2 = 0.f, s3 = 0.f;
#pragma unroll
            for (int p = 0; p < 8; p++) {
                s0 += __uint_as_float(w[p].x);
                s1 += __uint_as_float(w[p].y);
                s2 += __uint_as_float(w[p].z);
                s3 += __uint_as_float(w[p].w);
            }
            const int bb = idx / 72, c4 = idx - bb * 72;
            uint2 pk;
            pk.x = pack_bf16(silu_f(bfr(s0)), silu_f(bfr(s1)));
            pk.y = pack_bf16(silu_f(bfr(s2)), silu_f(bfr(s3)));
            *reinterpret_cast<uint2*>(h_s + bb * 296 + 4 * c4) = pk;
        }
        if (tid == 0) TS(10);
    }
    bar_cons();

    {
        const int hh = gid & 1;
        float M = ml_s[hh * 8];
#pragma unroll
        for (int w = 1; w < 8; w++) M = fmaxf(M, ml_s[hh * 8 + w]);
        const float l2e = 1.4426950408889634f;
        float lsum = 0.f;
#pragma unroll
        for (int nt = 0; nt < 8; nt++) {
            const float p0 = exp2f((sc[nt][0] - M) * l2e);
            const float p1 = exp2f((sc[nt][1] - M) * l2e);
            lsum += p0 + p1;
            if (gid < 2) *reinterpret_cast<uint32_t*>(p_s + gid * 520 + 64 * warp + 8 * nt + 2 * tig) = pack_bf16(p0, p1);
        }
        lsum += __shfl_xor_sync(0xffffffffu, lsum, 1);
        lsum += __shfl_xor_sync(0xffffffffu, lsum, 2);
        if (lane == 0 || lane == 4) ml_s[16 + (lane >> 2) * 8 + warp] = lsum;
    }
    bar_cons();

    {
        float oc[2][4] = {{0.f, 0.f, 0.f, 0.f}, {0.f, 0.f, 0.f, 0.f}};
        const int cg = 2 * warp + (lm_j & 1);
        const uint32_t vbase = sbase + OFF_KV + (cg >> 3) * 8192 + ((lm_j >> 1) * 8 + lm_i) * 128 + (((cg & 7) ^ lm_i) << 4);
        const __nv_bfloat16* pp = p_s + (gid & 1) * 520 + 2 * tig;
#pragma unroll 1
        for (int c = 0; c < 8; c++) {
            uint32_t pb[8];
#pragma unroll
            for (int j = 0; j < 8; j++) {
                pb[j] = *reinterpret_cast<const uint32_t*>(pp + 64 * c + 8 * j);
                if (gid >= 2) pb[j] = 0u;
            }
            mbar_wait(bar_full + 8 * (12 + c), 0);
            if (tid == 0 && c == 0) TS(6);
            if (tid == 0 && c == 7) TS(8);
#pragma unroll
            for (int ks = 0; ks < 4; ks++) {
                uint32_t a0, a1, a2, a3;
                ldsm_x4_t(vbase + c * kSlotBytes + ks * 16 * 128, a0, a1, a2, a3);
                mma16816(oc[ks & 1], a0, a1, a2, a3, pb[2 * ks], pb[2 * ks + 1]);
            }
        }
        uint32_t* od = g_opart + (size_t)((g * kB + b) * 2 + half) * 272;
        if (tig == 0) {
            const int d = 16 * warp + gid;
            st_word(od + d, tagw(oc[0][0] + oc[1][0], flag));
            st_word(od + 136 + d, tagw(oc[0][1] + oc[1][1], flag));
            st_word(od + d + 8, tagw(oc[0][2] + oc[1][2], flag));
            st_word(od + 136 + d + 8, tagw(oc[0][3] + oc[1][3], flag));
        }
        if (warp == 0 && (lane == 1 || lane == 2)) {
            const int hh = lane - 1;
            float M = ml_s[hh * 8], L = ml_s[16 + hh * 8];
#pragma unroll
            for (int w = 1; w < 8; w++) {
                M = fmaxf(M, ml_s[hh * 8 + w]);
                L += ml_s[16 + hh * 8 + w];
            }
            st_word2(od + hh * 136 + 128, tagw(M, flag), tagw(L, flag));
        }
    }
    if (tid == 0) TS(13);

    {
        mbar_wait(bar_full + 8 * 20, 0);
        mbar_wait(bar_full + 8 * 21, 0);
        if (tid == 0) TS(11);
        for (int nt = 7 - warp; nt < 9; nt += 8) {
            float c[4];
            gemv3_tile<18, 296>(sbase + OFF_B, h_s, nt, lane, c);
            if (gid < 4)
                st_word2(g_fpart + (size_t)(((r * 9 + nt) * 2 + 1) * kGroups + g) * 32 + gid * 8 + 2 * tig,
                         tagw(c[0], flag), tagw(c[1], flag));
        }
        if (tid == 0) TS(12);
    }

    {
        const int head = tid >> 7;
        const uint32_t* src = g_opart + (size_t)(g * kB * 2) * 272 + head * 136;
        uint32_t wv[8];
        uint2 wml[8];
        for (int it = 0; it < kSpinLimit; it++) {
            uint32_t bad = 0;
#pragma unroll
            for (int p = 0; p < 8; p++) {
                wv[p] = ld_word(src + p * 272 + (tid & 127));
                wml[p] = ld_word2(src + p * 272 + 128);
                bad |= (wv[p] ^ flag) | (wml[p].x ^ flag) | (wml[p].y ^ flag);
            }
            if (!(bad & 1u)) break;
        }
#pragma unroll
        for (int bb = 0; bb < 4; bb++) {
            const float m0 = __uint_as_float(wml[2 * bb].x), m1 = __uint_as_float(wml[2 * bb + 1].x);
            const float MM = fmaxf(m0, m1);
            const float e0 = exp2f((m0 - MM) * 1.4426950408889634f), e1 = exp2f((m1 - MM) * 1.4426950408889634f);
            const float LL = e0 * __uint_as_float(wml[2 * bb].y) + e1 * __uint_as_float(wml[2 * bb + 1].y);
            const float OO = e0 * __uint_as_float(wv[2 * bb]) + e1 * __uint_as_float(wv[2 * bb + 1]);
            o_s[bb * 264 + tid] = __float2bfloat16_rn(OO / LL);
        }
    }
    mbar_wait(bar_full + 8 * 22, 0);
    mbar_wait(bar_full + 8 * 23, 0);
    asm volatile("bar.sync 3, 288;" ::: "memory");
    if (tid == 0) TS(9);

    {
        float c[4];
        gemv3_tile<16, 264>(sbase + OFF_A, o_s, warp, lane, c);
        if (gid < 4)
            st_word2(g_fpart + (size_t)(((r * 9 + warp) * 2 + 0) * kGroups + g) * 32 + gid * 8 + 2 * tig,
                     tagw(c[0], flag), tagw(c[1], flag));
    }
    if (tid == 0) TS(15);

    if (cta < kFinalCons && warp == 0) {
        const int gh = lane >> 4, which = (lane >> 3) & 1, bc = lane & 7;
        const uint32_t* src = g_fpart + (size_t)cta * 1024 + (which * kGroups + gh * 8) * 32 + bc * 4;
        uint4 w[8];
        for (int it = 0; it < kSpinLimit; it++) {
            uint32_t bad = 0;
#pragma unroll
            for (int i = 0; i < 8; i++) {
                w[i] = ld_word4(src + i * 32);
                bad |= (w[i].x ^ flag) | (w[i].y ^ flag) | (w[i].z ^ flag) | (w[i].w ^ flag);
            }
            if (!__any_sync(0xffffffffu, bad & 1u)) break;
        }
        if (tid == 0) TS(16);
        float v[4] = {0.f, 0.f, 0.f, 0.f};
#pragma unroll
        for (int i = 0; i < 8; i++) {
            v[0] += __uint_as_float(w[i].x);
            v[1] += __uint_as_float(w[i].y);
            v[2] += __uint_as_float(w[i].z);
            v[3] += __uint_as_float(w[i].w);
        }
        float gsum[4];
#pragma unroll
        for (int j = 0; j < 4; j++) {
            v[j] += __shfl_xor_sync(0xffffffffu, v[j], 16);
            gsum[j] = __shfl_xor_sync(0xffffffffu, v[j], 8);
        }
        if (lane < 8) {
            float o4[4];
#pragma unroll
            for (int j = 0; j < 4; j++) {
                const float gg = bfr(silu_f(bfr(gsum[j])));
                const float sg = bfr(bfr(v[j]) * gg);
                o4[j] = x_fin[j] + sg;
            }
            const int rc = cta / 9, ntc = cta - 9 * rc;
            uint2 pk;
            pk.x = pack_bf16(o4[0], o4[1]);
            pk.y = pack_bf16(o4[2], o4[3]);
            *reinterpret_cast<uint2*>(out + (lane >> 1) * kD + kCols3 * rc + 8 * ntc + (lane & 1) * 4) = pk;
        }
        if (tid == 0) TS(17);
        if (cta == 0 && tid == 0) {
            asm volatile("st.relaxed.gpu.global.u32 [%0], %1;" ::"l"(&g_epoch), "r"(epoch + 1u) : "memory");
        }
    }
}

typedef CUresult (*PFN_encodeTiled)(CUtensorMap*, CUtensorMapDataType, cuuint32_t, void*, const cuuint64_t*,
                                    const cuuint64_t*, const cuuint32_t*, const cuuint32_t*, CUtensorMapInterleave,
                                    CUtensorMapSwizzle, CUtensorMapL2promotion, CUtensorMapFloatOOBfill);

void make_map(PFN_encodeTiled enc, CUtensorMap* map, const void* ptr, uint64_t cols, uint64_t rows, uint32_t box_c,
              uint32_t box_r, CUtensorMapSwizzle swz, CUtensorMapL2promotion promo) {
    cuuint64_t gdim[2] = {cols, rows};
    cuuint64_t gstr[1] = {cols * 2};
    cuuint32_t box[2] = {box_c, box_r};
    cuuint32_t estr[2] = {1, 1};
    enc(map, CU_TENSOR_MAP_DATA_TYPE_BFLOAT16, 2, const_cast<void*>(ptr), gdim, gstr, box, estr,
        CU_TENSOR_MAP_INTERLEAVE_NONE, swz, promo, CU_TENSOR_MAP_FLOAT_OOB_FILL_NONE);
}

}

extern "C" void kernel_launch(void* const* d_in, const int* in_sizes, int n_in, void* d_out, int out_size) {
    (void)in_sizes;
    (void)n_in;
    (void)out_size;
    static PFN_encodeTiled enc = nullptr;
    if (!enc) {
        void* fn = nullptr;
        cudaDriverEntryPointQueryResult st;
        cudaGetDriverEntryPoint("cuTensorMapEncodeTiled", &fn, cudaEnableDefault, &st);
        enc = (PFN_encodeTiled)fn;
        cudaFuncSetAttribute(fused_decode_kernel, cudaFuncAttributeMaxDynamicSharedMemorySize, SMEM_BYTES);
    }
    CUtensorMap kmap, vmap, womap, w2map, wqmap, w1map;
    make_map(enc, &wqmap, d_in[3], kNQ, kD, 64, kRows1, CU_TENSOR_MAP_SWIZZLE_128B, CU_TENSOR_MAP_L2_PROMOTION_L2_256B);
    make_map(enc, &w1map, d_in[6], kF, kD, 72, kRows1, CU_TENSOR_MAP_SWIZZLE_NONE, CU_TENSOR_MAP_L2_PROMOTION_L2_256B);
    make_map(enc, &kmap, d_in[1], kDh, (uint64_t)kB * kHkv * kSk, 64, kChunkKeys, CU_TENSOR_MAP_SWIZZLE_128B,
             CU_TENSOR_MAP_L2_PROMOTION_L2_256B);
    make_map(enc, &vmap, d_in[2], kDh, (uint64_t)kB * kHkv * kSk, 64, kChunkKeys, CU_TENSOR_MAP_SWIZZLE_128B,
             CU_TENSOR_MAP_L2_PROMOTION_L2_256B);
    make_map(enc, &womap, d_in[4], kD, kNQ, kCols3, 128, CU_TENSOR_MAP_SWIZZLE_NONE,
             CU_TENSOR_MAP_L2_PROMOTION_L2_128B);
    make_map(enc, &w2map, d_in[7], kD, kF, kCols3, 144, CU_TENSOR_MAP_SWIZZLE_NONE,
             CU_TENSOR_MAP_L2_PROMOTION_L2_128B);
    fused_decode_kernel<<<kCTAs, 288, SMEM_BYTES>>>(kmap, vmap, womap, w2map, wqmap, w1map,
                                                    (const __nv_bfloat16*)d_in[0], (__nv_bfloat16*)d_out);
}
```

```cpp
#include <cuda_runtime.h>
#include <cuda_bf16.h>
#include <cuda.h>
#include <stdint.h>

namespace {

constexpr int kB = 4, kD = 576, kHkv = 16, kSk = 4096, kDh = 128, kWin = 1024, kF = 4608;
constexpr int kNQ = 4096;
constexpr int kGroups = 16, kRanks = 8, kCTAs = 128;
constexpr int kRows1 = 72;
constexpr int kQCols = 256, kHCols = 288;
constexpr int kCols3 = 72;
constexpr int kChunkKeys = 64;
constexpr int kFinalCons = 72;

constexpr int kSlotBytes = 16384;
constexpr int OFF_KV = 0;
constexpr int STR_W3 = 144;
constexpr int BOX_WQ = kRows1 * 128;
constexpr int BOX_W1 = kRows1 * 144;
constexpr int OFF_A = 8 * kSlotBytes;
constexpr int SZ_A = 4 * BOX_WQ;
constexpr int OFF_B = OFF_A + SZ_A;
constexpr int SZ_B = 4 * BOX_W1;
constexpr int OFF_XN = OFF_B + SZ_B;
constexpr int OFF_Q = OFF_XN + 640;
constexpr int OFF_H = OFF_Q + 544;
constexpr int OFF_O = OFF_H + 4 * 296 * 2;
constexpr int OFF_P = OFF_O + 4 * 264 * 2;
constexpr int OFF_ML = OFF_P + 2 * 520 * 2;
constexpr int OFF_STG = OFF_ML + 128;
constexpr int OFF_BAR = OFF_STG + 1024;
constexpr int SMEM_USED = OFF_BAR + 288;
constexpr int SMEM_BYTES = SMEM_USED + 1024;

static_assert(OFF_A % 128 == 0 && OFF_B % 128 == 0, "align");
static_assert(OFF_BAR % 8 == 0 && OFF_STG % 16 == 0, "align");
static_assert(SMEM_BYTES <= 232448, "smem");

__device__ __align__(128) uint32_t g_qpart[kGroups * kRanks * kB * kQCols];
__device__ __align__(128) uint32_t g_hpart[kGroups * kRanks * kB * kHCols];
__device__ __align__(128) uint32_t g_opart[kGroups * kB * 2 * 2 * 136];
__device__ __align__(128) uint32_t g_fpart[kFinalCons * 2 * kGroups * 32];
__device__ uint32_t g_epoch;

constexpr int kSpinLimit = 1 << 22;
#define KWINDOW 4
constexpr int kWindow = KWINDOW;

#define ORDER 3
#define G_FIRST (ORDER == 1 || ORDER == 2 || ORDER == 4)
__constant__ int c_order[24] = {0, 1, 2, 3, 4, 5, 6, 7, 8, 9, 10, 11, 12, 13, 14, 15, 16, 17, 18, 19, 20, 21, 22, 23};

#define TS(k)
#define TS2(k)

__device__ __forceinline__ uint32_t smem_u32(const void* p) {
    return (uint32_t)__cvta_generic_to_shared(p);
}
__device__ __forceinline__ void mbar_init(uint32_t bar, uint32_t count) {
    asm volatile("mbarrier.init.shared::cta.b64 [%0], %1;" ::"r"(bar), "r"(count) : "memory");
}
__device__ __forceinline__ void mbar_expect_tx(uint32_t bar, uint32_t bytes) {
    asm volatile("mbarrier.arrive.expect_tx.shared::cta.b64 _, [%0], %1;" ::"r"(bar), "r"(bytes) : "memory");
}
__device__ __forceinline__ void mbar_arrive(uint32_t bar) {
    asm volatile("mbarrier.arrive.shared::cta.b64 _, [%0];" ::"r"(bar) : "memory");
}
__device__ __forceinline__ bool mbar_try_wait(uint32_t bar, uint32_t parity) {
    uint32_t ok;
    asm volatile(
        "{\n .reg .pred p;\n mbarrier.try_wait.parity.shared::cta.b64 p, [%1], %2;\n selp.u32 %0, 1, 0, p;\n}"
        : "=r"(ok)
        : "r"(bar), "r"(parity)
        : "memory");
    return ok != 0;
}
__device__ __forceinline__ void mbar_wait(uint32_t bar, uint32_t parity) {
    for (int i = 0; i < kSpinLimit; i++) {
        if (mbar_try_wait(bar, parity)) break;
    }
}
__device__ __forceinline__ void bulk_g2s(uint32_t dst, const void* src, uint32_t bytes, uint32_t bar) {
    asm volatile(
        "cp.async.bulk.shared::cluster.global.mbarrier::complete_tx::bytes [%0], [%1], %2, [%3];" ::"r"(dst),
        "l"(src), "r"(bytes), "r"(bar)
        : "memory");
}
__device__ __forceinline__ void tma_2d_ef(uint32_t dst, const CUtensorMap* map, int c0, int c1, uint32_t bar) {
    uint64_t pol;
    asm volatile("createpolicy.fractional.L2::evict_first.b64 %0, 1.0;" : "=l"(pol));
    asm volatile(
        "cp.async.bulk.tensor.2d.shared::cluster.global.mbarrier::complete_tx::bytes.L2::cache_hint [%0], [%1, {%3, %4}], [%2], %5;" ::"r"(dst),
        "l"(map), "r"(bar), "r"(c0), "r"(c1), "l"(pol)
        : "memory");
}
__device__ __forceinline__ void tma_2d(uint32_t dst, const CUtensorMap* map, int c0, int c1, uint32_t bar) {
    asm volatile(
        "cp.async.bulk.tensor.2d.shared::cluster.global.mbarrier::complete_tx::bytes [%0], [%1, {%3, %4}], [%2];" ::"r"(dst),
        "l"(map), "r"(bar), "r"(c0), "r"(c1)
        : "memory");
}
__device__ __forceinline__ void ldsm_x4(uint32_t addr, uint32_t& r0, uint32_t& r1, uint32_t& r2, uint32_t& r3) {
    asm volatile("ldmatrix.sync.aligned.m8n8.x4.shared.b16 {%0,%1,%2,%3}, [%4];"
                 : "=r"(r0), "=r"(r1), "=r"(r2), "=r"(r3)
                 : "r"(addr)
                 : "memory");
}
__device__ __forceinline__ void ldsm_x4_t(uint32_t addr, uint32_t& r0, uint32_t& r1, uint32_t& r2, uint32_t& r3) {
    asm volatile("ldmatrix.sync.aligned.m8n8.x4.trans.shared.b16 {%0,%1,%2,%3}, [%4];"
                 : "=r"(r0), "=r"(r1), "=r"(r2), "=r"(r3)
                 : "r"(addr)
                 : "memory");
}
__device__ __forceinline__ void ldsm_x2_t(uint32_t addr, uint32_t& r0, uint32_t& r1) {
    asm volatile("ldmatrix.sync.aligned.m8n8.x2.trans.shared.b16 {%0,%1}, [%2];"
                 : "=r"(r0), "=r"(r1)
                 : "r"(addr)
                 : "memory");
}
__device__ __forceinline__ void mma16816(float (&c)[4], uint32_t a0, uint32_t a1, uint32_t a2, uint32_t a3,
                                         uint32_t b0, uint32_t b1) {
    asm volatile(
        "mma.sync.aligned.m16n8k16.row.col.f32.bf16.bf16.f32 {%0,%1,%2,%3}, {%4,%5,%6,%7}, {%8,%9}, {%0,%1,%2,%3};"
        : "+f"(c[0]), "+f"(c[1]), "+f"(c[2]), "+f"(c[3])
        : "r"(a0), "r"(a1), "r"(a2), "r"(a3), "r"(b0), "r"(b1));
}
__device__ __forceinline__ void mma1688(float (&c)[4], uint32_t a0, uint32_t a1, uint32_t b0) {
    asm volatile("mma.sync.aligned.m16n8k8.row.col.f32.bf16.bf16.f32 {%0,%1,%2,%3}, {%4,%5}, {%6}, {%0,%1,%2,%3};"
                 : "+f"(c[0]), "+f"(c[1]), "+f"(c[2]), "+f"(c[3])
                 : "r"(a0), "r"(a1), "r"(b0));
}
__device__ __forceinline__ void bar_cons() { asm volatile("bar.sync 1, 256;" ::: "memory"); }

__device__ __forceinline__ float bfr(float x) { return __bfloat162float(__float2bfloat16_rn(x)); }
__device__ __forceinline__ uint32_t pack_bf16(float lo, float hi) {
    __nv_bfloat162 v = __floats2bfloat162_rn(lo, hi);
    return *reinterpret_cast<uint32_t*>(&v);
}
__device__ __forceinline__ uint32_t tagw(float v, uint32_t flag) { return (__float_as_uint(v) & ~1u) | flag; }
__device__ __forceinline__ void st_word(uint32_t* p, uint32_t v) {
    asm volatile("st.relaxed.gpu.global.u32 [%0], %1;" ::"l"(p), "r"(v) : "memory");
}
__device__ __forceinline__ void st_word2(uint32_t* p, uint32_t v0, uint32_t v1) {
    asm volatile("st.relaxed.gpu.global.v2.u32 [%0], {%1,%2};" ::"l"(p), "r"(v0), "r"(v1) : "memory");
}
__device__ __forceinline__ void st_word4(uint32_t* p, uint32_t v) {
    asm volatile("st.relaxed.gpu.global.v4.u32 [%0], {%1,%1,%1,%1};" ::"l"(p), "r"(v) : "memory");
}
__device__ __forceinline__ void st_word4v(uint32_t* p, uint32_t a, uint32_t b, uint32_t c, uint32_t d) {
    asm volatile("st.relaxed.gpu.global.v4.u32 [%0], {%1,%2,%3,%4};" ::"l"(p), "r"(a), "r"(b), "r"(c), "r"(d) : "memory");
}
__device__ __forceinline__ uint32_t ld_word(const uint32_t* p) {
    uint32_t v;
    asm volatile("ld.relaxed.gpu.global.u32 %0, [%1];" : "=r"(v) : "l"(p) : "memory");
    return v;
}
__device__ __forceinline__ uint2 ld_word2(const uint32_t* p) {
    uint2 v;
    asm volatile("ld.relaxed.gpu.global.v2.u32 {%0,%1}, [%2];" : "=r"(v.x), "=r"(v.y) : "l"(p) : "memory");
    return v;
}
__device__ __forceinline__ uint4 ld_word4(const uint32_t* p) {
    uint4 v;
    asm volatile("ld.relaxed.gpu.global.v4.u32 {%0,%1,%2,%3}, [%4];"
                 : "=r"(v.x), "=r"(v.y), "=r"(v.z), "=r"(v.w)
                 : "l"(p)
                 : "memory");
    return v;
}
__device__ __forceinline__ float silu_f(float x) { return x / (1.0f + __expf(-x)); }

template <int KSTEPS, int ASTRIDE>
__device__ __forceinline__ void gemv3_tile(uint32_t wbuf, const __nv_bfloat16* act, int nt, int lane, float (&c)[4]) {
    const int gid = lane >> 2, tig = lane & 3, lm_i = lane & 7, lm_j = lane >> 3;
    const uint32_t wb = wbuf + (8 * lm_j + lm_i) * STR_W3 + nt * 16;
    const __nv_bfloat16* ap = act + (gid & 3) * ASTRIDE + 2 * tig;
    float acc[4][4];
#pragma unroll
    for (int i = 0; i < 4; i++) acc[i][0] = acc[i][1] = acc[i][2] = acc[i][3] = 0.f;
#pragma unroll
    for (int kk = 0; kk < KSTEPS / 2; kk++) {
        uint32_t b0, b1, b2, b3;
        ldsm_x4_t(wb + kk * 32 * STR_W3, b0, b1, b2, b3);
        uint32_t a0 = *reinterpret_cast<const uint32_t*>(ap + 32 * kk);
        uint32_t a2 = *reinterpret_cast<const uint32_t*>(ap + 32 * kk + 8);
        uint32_t a4 = *reinterpret_cast<const uint32_t*>(ap + 32 * kk + 16);
        uint32_t a6 = *reinterpret_cast<const uint32_t*>(ap + 32 * kk + 24);
        if (gid >= 4) a0 = a2 = a4 = a6 = 0u;
        mma16816(acc[(2 * kk) & 3], a0, 0u, a2, 0u, b0, b1);
        mma16816(acc[(2 * kk + 1) & 3], a4, 0u, a6, 0u, b2, b3);
    }
    c[0] = (acc[0][0] + acc[1][0]) + (acc[2][0] + acc[3][0]);
    c[1] = (acc[0][1] + acc[1][1]) + (acc[2][1] + acc[3][1]);
    c[2] = c[3] = 0.f;
}

__global__ void __launch_bounds__(288, 1)
fused_decode_kernel(const __grid_constant__ CUtensorMap kmap, const __grid_constant__ CUtensorMap vmap,
                    const __grid_constant__ CUtensorMap womap, const __grid_constant__ CUtensorMap w2map,
                    const __grid_constant__ CUtensorMap wqmap, const __grid_constant__ CUtensorMap w1map,
                    const __nv_bfloat16* __restrict__ x, __nv_bfloat16* __restrict__ out) {
    extern __shared__ uint8_t smem_raw[];
    const uint32_t raw_u32 = smem_u32(smem_raw);
    const uint32_t sbase = (raw_u32 + 1023u) & ~1023u;
    uint8_t* sgen = smem_raw + (sbase - raw_u32);

    const int tid = threadIdx.x, warp = tid >> 5, lane = tid & 31;
    const int cta = blockIdx.x;
    const int g = cta >> 3, r = cta & 7;
    const int b = r >> 1, half = r & 1;

    const uint32_t bar_full = sbase + OFF_BAR;
    const uint32_t bar_empty = sbase + OFF_BAR + 24 * 8;
    const uint32_t bar_s1 = sbase + OFF_BAR + 32 * 8;

    const int kv_row0 = (b * kHkv + g) * kSk + (kSk - kWin) + half * 512;

    if (warp == 8) {
        if (lane == 0) {
            TS(0);
            for (int i = 0; i < 32; i++) mbar_init(bar_full + 8 * i, 1);
            mbar_init(bar_s1, 8);
            asm volatile("fence.mbarrier_init.release.cluster;" ::: "memory");
            asm volatile("fence.proxy.async.shared::cta;" ::: "memory");
        }
        __syncwarp();
        asm volatile("bar.arrive 2, 288;" ::: "memory");
#pragma unroll 1
        for (int n = 0; n < 24; n++) {
            const int u = c_order[n];
            if (n >= kWindow) mbar_wait(bar_full + 8 * c_order[n - kWindow], 0);
            const uint32_t bar = bar_full + 8 * u;
            if (u < 2) {
                if (lane == 0) {
                    mbar_expect_tx(bar, 2 * BOX_WQ);
                    tma_2d(sbase + OFF_A + (2 * u) * BOX_WQ, &wqmap, kQCols * g + 128 * u, kRows1 * r, bar);
                    tma_2d(sbase + OFF_A + (2 * u + 1) * BOX_WQ, &wqmap, kQCols * g + 128 * u + 64, kRows1 * r, bar);
                }
            } else if (u < 4) {
                if (lane == 0) {
                    mbar_expect_tx(bar, 2 * BOX_W1);
                    tma_2d(sbase + OFF_B + (2 * u - 4) * BOX_W1, &w1map, kHCols * g + 144 * (u - 2), kRows1 * r, bar);
                    tma_2d(sbase + OFF_B + (2 * u - 3) * BOX_W1, &w1map, kHCols * g + 144 * (u - 2) + 72, kRows1 * r, bar);
                }
            } else if (u < 20) {
                const int c = (u - 4) & 7;
                if (u >= 12) mbar_wait(bar_empty + 8 * c, 0);
                if (lane == 0) {
                    const CUtensorMap* mp = u >= 12 ? &vmap : &kmap;
                    mbar_expect_tx(bar, kSlotBytes);
                    tma_2d_ef(sbase + OFF_KV + c * kSlotBytes, mp, 0, kv_row0 + kChunkKeys * c, bar);
                    tma_2d_ef(sbase + OFF_KV + c * kSlotBytes + 8192, mp, 64, kv_row0 + kChunkKeys * c, bar);
                }
            } else if (u < 22) {
                mbar_wait(bar_s1, 0);
                if (lane == 0) {
                    mbar_expect_tx(bar, 144 * STR_W3);
                    tma_2d(sbase + OFF_B + (u - 20) * 144 * STR_W3, &w2map, kCols3 * r, kHCols * g + 144 * (u - 20), bar);
                }
            } else {
                mbar_wait(bar_s1, 0);
                if (lane == 0) {
                    mbar_expect_tx(bar, 128 * STR_W3);
                    tma_2d(sbase + OFF_A + (u - 22) * 128 * STR_W3, &womap, kCols3 * r, kQCols * g + 128 * (u - 22), bar);
                }
            }
            if (lane == 0) TS2(n);
            __syncwarp();
        }
        asm volatile("bar.sync 3, 288;" ::: "memory");
        mbar_wait(bar_full + 8 * 22, 0);
        mbar_wait(bar_full + 8 * 23, 0);
        const uint32_t flag_p = *reinterpret_cast<volatile uint32_t*>(sgen + OFF_BAR + 280);
        {
            float c[4];
            gemv3_tile<16, 264>(sbase + OFF_A, reinterpret_cast<const __nv_bfloat16*>(sgen + OFF_O), 8, lane, c);
            if ((lane >> 2) < 4)
                st_word2(g_fpart + (size_t)(((r * 9 + 8) * 2 + 0) * kGroups + g) * 32 + (lane >> 2) * 8 + 2 * (lane & 3),
                         tagw(c[0], flag_p), tagw(c[1], flag_p));
        }
        return;
    }

    uint32_t epoch;
    asm volatile("ld.relaxed.gpu.global.u32 %0, [%1];" : "=r"(epoch) : "l"(&g_epoch) : "memory");
    uint32_t xw[9];
    if (warp < 4) {
        const uint32_t* xr = reinterpret_cast<const uint32_t*>(x + warp * kD);
#pragma unroll
        for (int i = 0; i < 9; i++) xw[i] = __ldg(xr + lane + 32 * i);
    }
    float x_fin[4] = {0.f, 0.f, 0.f, 0.f};
    if (cta < kFinalCons && tid < 8) {
        const int rc = cta / 9, ntc = cta - 9 * rc;
        const uint2 xv = __ldg(reinterpret_cast<const uint2*>(x + (tid >> 1) * kD + kCols3 * rc + 8 * ntc + (tid & 1) * 4));
        x_fin[0] = __uint_as_float(xv.x << 16);
        x_fin[1] = __uint_as_float(xv.x & 0xffff0000u);
        x_fin[2] = __uint_as_float(xv.y << 16);
        x_fin[3] = __uint_as_float(xv.y & 0xffff0000u);
    }
    const uint32_t flag = (epoch + 1u) & 1u;

    __nv_bfloat16* xn_s = reinterpret_cast<__nv_bfloat16*>(sgen + OFF_XN);
    __nv_bfloat16* q_s = reinterpret_cast<__nv_bfloat16*>(sgen + OFF_Q);
    __nv_bfloat16* h_s = reinterpret_cast<__nv_bfloat16*>(sgen + OFF_H);
    __nv_bfloat16* o_s = reinterpret_cast<__nv_bfloat16*>(sgen + OFF_O);
    __nv_bfloat16* p_s = reinterpret_cast<__nv_bfloat16*>(sgen + OFF_P);
    float* ml_s = reinterpret_cast<float*>(sgen + OFF_ML);

    if (tid == 0) *reinterpret_cast<volatile uint32_t*>(sgen + OFF_BAR + 280) = flag;
    {
        const uint32_t inv = flag ^ 1u;
        st_word4(g_qpart + (size_t)(g * kRanks + r) * kB * kQCols + 4 * tid, inv);
        uint32_t* hd = g_hpart + (size_t)(g * kRanks + r) * kB * kHCols;
        for (int i = tid; i < kB * kHCols / 4; i += 256) st_word4(hd + 4 * i, inv);
        if (tid < 68) st_word4(g_opart + (size_t)((g * kB + b) * 2 + half) * 272 + 4 * tid, inv);
        if (tid >= 96 && tid < 96 + 144) {
            const int i = tid - 96;
            const int nt = i >> 4, wh = (i >> 3) & 1, c4 = i & 7;
            st_word4(g_fpart + (size_t)(((r * 9 + nt) * 2 + wh) * kGroups + g) * 32 + 4 * c4, inv);
        }
    }

    if (warp < 4) {
        float v[18];
        float sum = 0.f;
#pragma unroll
        for (int i = 0; i < 9; i++) {
            v[2 * i] = __uint_as_float(xw[i] << 16);
            v[2 * i + 1] = __uint_as_float(xw[i] & 0xffff0000u);
            sum += v[2 * i] + v[2 * i + 1];
        }
#pragma unroll
        for (int o = 16; o > 0; o >>= 1) sum += __shfl_xor_sync(0xffffffffu, sum, o);
        const float mean = sum * (1.0f / kD);
        float sq = 0.f;
#pragma unroll
        for (int i = 0; i < 18; i++) {
            float d = v[i] - mean;
            sq += d * d;
        }
#pragma unroll
        for (int o = 16; o > 0; o >>= 1) sq += __shfl_xor_sync(0xffffffffu, sq, o);
        const float m_bf = bfr(mean);
        const float v_bf = bfr(sq * (1.0f / kD));
        const float den = bfr(sqrtf(bfr(v_bf + 1e-5f)));
#pragma unroll
        for (int i = 0; i < 9; i++) {
            int e = 2 * (lane + 32 * i) - kRows1 * r;
            if (e >= 0 && e < kRows1) {
                float a0 = bfr(v[2 * i] - m_bf) / den;
                float a1 = bfr(v[2 * i + 1] - m_bf) / den;
                *reinterpret_cast<uint32_t*>(xn_s + warp * 80 + e) = pack_bf16(a0, a1);
            }
        }
    }
    asm volatile("bar.sync 2, 288;" ::: "memory");
    if (tid == 0) TS(1);

    const int gid = lane >> 2, tig = lane & 3;
    const int lm_i = lane & 7, lm_j = lane >> 3;

    {
        uint32_t bx[9];
#pragma unroll
        for (int ks = 0; ks < 4; ks++) {
            bx[2 * ks] = gid < 4 ? *reinterpret_cast<const uint32_t*>(xn_s + gid * 80 + 16 * ks + 2 * tig) : 0u;
            bx[2 * ks + 1] = gid < 4 ? *reinterpret_cast<const uint32_t*>(xn_s + gid * 80 + 16 * ks + 8 + 2 * tig) : 0u;
        }
        bx[8] = gid < 4 ? *reinterpret_cast<const uint32_t*>(xn_s + gid * 80 + 64 + 2 * tig) : 0u;

        mbar_wait(bar_full + 8 * 0, 0);
        mbar_wait(bar_full + 8 * 1, 0);
        if (tid == 0) TS(2);
        uint32_t* qdst = g_qpart + (size_t)(g * kRanks + r) * kB * kQCols;
#pragma unroll
        for (int t = 0; t < 2; t++) {
            const int m0 = 16 * (warp + 8 * t);
            float c[4] = {0.f, 0.f, 0.f, 0.f};
            const int cgp = (m0 >> 3) + (lm_j & 1);
            const uint32_t bbase = sbase + OFF_A + (cgp >> 3) * BOX_WQ + (((cgp & 7) ^ lm_i) << 4);
            const uint32_t abase = bbase + (lm_i + (lm_j >> 1) * 8) * 128;
#pragma unroll
            for (int ks = 0; ks < 4; ks++) {
                uint32_t a0, a1, a2, a3;
                ldsm_x4_t(abase + ks * 16 * 128, a0, a1, a2, a3);
                mma16816(c, a0, a1, a2, a3, bx[2 * ks], bx[2 * ks + 1]);
            }
            {
                uint32_t a0, a1;
                ldsm_x2_t(bbase + (64 + lm_i) * 128, a0, a1);
                mma1688(c, a0, a1, bx[8]);
            }
            if (tig < 2) {
                const int col = m0 + gid;
                st_word(qdst + (2 * tig) * kQCols + col, tagw(c[0], flag));
                st_word(qdst + (2 * tig + 1) * kQCols + col, tagw(c[1], flag));
                st_word(qdst + (2 * tig) * kQCols + col + 8, tagw(c[2], flag));
                st_word(qdst + (2 * tig + 1) * kQCols + col + 8, tagw(c[3], flag));
            }
        }
        mbar_wait(bar_full + 8 * 2, 0);
        mbar_wait(bar_full + 8 * 3, 0);
        if (tid == 0) TS(3);
        uint32_t* hdst = g_hpart + (size_t)(g * kRanks + r) * kB * kHCols;
        for (int t = warp; t < 18; t += 8) {
            const int m0 = 16 * t;
            float c[4] = {0.f, 0.f, 0.f, 0.f};
            const int cgp = (m0 >> 3) + (lm_j & 1);
            const int bx_ = cgp / 9;
            const uint32_t bbase = sbase + OFF_B + bx_ * BOX_W1 + (cgp - 9 * bx_) * 16;
            const uint32_t abase = bbase + (lm_i + (lm_j >> 1) * 8) * 144;
#pragma unroll
            for (int ks = 0; ks < 4; ks++) {
                uint32_t a0, a1, a2, a3;
                ldsm_x4_t(abase + ks * 16 * 144, a0, a1, a2, a3);
                mma16816(c, a0, a1, a2, a3, bx[2 * ks], bx[2 * ks + 1]);
            }
            {
                uint32_t a0, a1;
                ldsm_x2_t(bbase + (64 + lm_i) * 144, a0, a1);
                mma1688(c, a0, a1, bx[8]);
            }
            if (tig < 2) {
                const int col = m0 + gid;
                st_word(hdst + (2 * tig) * kHCols + col, tagw(c[0], flag));
                st_word(hdst + (2 * tig + 1) * kHCols + col, tagw(c[1], flag));
                st_word(hdst + (2 * tig) * kHCols + col + 8, tagw(c[2], flag));
                st_word(hdst + (2 * tig + 1) * kHCols + col + 8, tagw(c[3], flag));
            }
        }
    }
    __syncwarp();
    if (lane == 0) mbar_arrive(bar_s1);

    if (tid < 64) {
        const uint32_t* src = g_qpart + (size_t)(g * kRanks) * kB * kQCols + b * kQCols + 4 * tid;
        uint4 w[8];
        for (int it = 0; it < kSpinLimit; it++) {
            uint32_t bad = 0;
#pragma unroll
            for (int p = 0; p < 8; p++) {
                w[p] = ld_word4(src + p * kB * kQCols);
                bad |= (w[p].x ^ flag) | (w[p].y ^ flag) | (w[p].z ^ flag) | (w[p].w ^ flag);
            }
            if (!(bad & 1u)) break;
        }
        float s0 = 0.f, s1 = 0.f, s2 = 0.f, s3 = 0.f;
#pragma unroll
        for (int p = 0; p < 8; p++) {
            s0 += __uint_as_float(w[p].x);
            s1 += __uint_as_float(w[p].y);
            s2 += __uint_as_float(w[p].z);
            s3 += __uint_as_float(w[p].w);
        }
        uint2 pk;
        pk.x = pack_bf16(s0, s1);
        pk.y = pack_bf16(s2, s3);
        *reinterpret_cast<uint2*>(q_s + (tid >> 5) * 136 + 4 * (tid & 31)) = pk;
    }
    bar_cons();
    if (tid == 0) TS(4);

    float sc[8][2];
    {
        const uint32_t slot = sbase + OFF_KV + warp * kSlotBytes;
        uint32_t qa[16];
#pragma unroll
        for (int j = 0; j < 8; j++) {
            qa[2 * j] = gid < 2 ? *reinterpret_cast<const uint32_t*>(q_s + gid * 136 + 16 * j + 2 * tig) : 0u;
            qa[2 * j + 1] = gid < 2 ? *reinterpret_cast<const uint32_t*>(q_s + gid * 136 + 16 * j + 8 + 2 * tig) : 0u;
        }
        mbar_wait(bar_full + 8 * (4 + warp), 0);
        if (tid == 0) TS(5);
        if (tid == 224) TS(7);
        float mx = -INFINITY;
        const float scale = 0.08838834764831845f;
#pragma unroll
        for (int nt = 0; nt < 8; nt++) {
            float acc[4] = {0.f, 0.f, 0.f, 0.f};
#pragma unroll
            for (int kk = 0; kk < 4; kk++) {
                const int cg = 4 * kk + lm_j;
                const uint32_t addr =
                    slot + (cg >> 3) * 8192 + (8 * nt + lm_i) * 128 + (((cg & 7) ^ lm_i) << 4);
                uint32_t b0, b1, b2, b3;
                ldsm_x4(addr, b0, b1, b2, b3);
                mma16816(acc, qa[4 * kk], 0u, qa[4 * kk + 1], 0u, b0, b1);
                mma16816(acc, qa[4 * kk + 2], 0u, qa[4 * kk + 3], 0u, b2, b3);
            }
            sc[nt][0] = bfr(bfr(acc[0]) * scale);
            sc[nt][1] = bfr(bfr(acc[1]) * scale);
            mx = fmaxf(mx, fmaxf(sc[nt][0], sc[nt][1]));
        }
        __syncwarp();
        if (lane == 0) mbar_arrive(bar_empty + 8 * warp);
        mx = fmaxf(mx, __shfl_xor_sync(0xffffffffu, mx, 1));
        mx = fmaxf(mx, __shfl_xor_sync(0xffffffffu, mx, 2));
        if (lane == 0 || lane == 4) ml_s[(lane >> 2) * 8 + warp] = mx;
    }

    {
        for (int idx = tid; idx < kB * kHCols / 4; idx += 256) {
            const uint32_t* src = g_hpart + (size_t)(g * kRanks) * kB * kHCols + 4 * idx;
            uint4 w[8];
            for (int it = 0; it < kSpinLimit; it++) {
                uint32_t bad = 0;
#pragma unroll
                for (int p = 0; p < 8; p++) {
                    w[p] = ld_word4(src + p * kB * kHCols);
                    bad |= (w[p].x ^ flag) | (w[p].y ^ flag) | (w[p].z ^ flag) | (w[p].w ^ flag);
                }
                if (!(bad & 1u)) break;
            }
            float s0 = 0.f, s1 = 0.f, s2 = 0.f, s3 = 0.f;
#pragma unroll
            for (int p = 0; p < 8; p++) {
                s0 += __uint_as_float(w[p].x);
                s1 += __uint_as_float(w[p].y);
                s2 += __uint_as_float(w[p].z);
                s3 += __uint_as_float(w[p].w);
            }
            const int bb = idx / 72, c4 = idx - bb * 72;
            uint2 pk;
            pk.x = pack_bf16(silu_f(bfr(s0)), silu_f(bfr(s1)));
            pk.y = pack_bf16(silu_f(bfr(s2)), silu_f(bfr(s3)));
            *reinterpret_cast<uint2*>(h_s + bb * 296 + 4 * c4) = pk;
        }
        if (tid == 0) TS(10);
    }
    bar_cons();

    {
        const int hh = gid & 1;
        float M = ml_s[hh * 8];
#pragma unroll
        for (int w = 1; w < 8; w++) M = fmaxf(M, ml_s[hh * 8 + w]);
        const float l2e = 1.4426950408889634f;
        float lsum = 0.f;
#pragma unroll
        for (int nt = 0; nt < 8; nt++) {
            const float p0 = exp2f((sc[nt][0] - M) * l2e);
            const float p1 = exp2f((sc[nt][1] - M) * l2e);
            lsum += p0 + p1;
            if (gid < 2) *reinterpret_cast<uint32_t*>(p_s + gid * 520 + 64 * warp + 8 * nt + 2 * tig) = pack_bf16(p0, p1);
        }
        lsum += __shfl_xor_sync(0xffffffffu, lsum, 1);
        lsum += __shfl_xor_sync(0xffffffffu, lsum, 2);
        if (lane == 0 || lane == 4) ml_s[16 + (lane >> 2) * 8 + warp] = lsum;
    }
    bar_cons();

    {
        float oc[2][4] = {{0.f, 0.f, 0.f, 0.f}, {0.f, 0.f, 0.f, 0.f}};
        const int cg = 2 * warp + (lm_j & 1);
        const uint32_t vbase = sbase + OFF_KV + (cg >> 3) * 8192 + ((lm_j >> 1) * 8 + lm_i) * 128 + (((cg & 7) ^ lm_i) << 4);
        const __nv_bfloat16* pp = p_s + (gid & 1) * 520 + 2 * tig;
#pragma unroll 1
        for (int c = 0; c < 8; c++) {
            uint32_t pb[8];
#pragma unroll
            for (int j = 0; j < 8; j++) {
                pb[j] = *reinterpret_cast<const uint32_t*>(pp + 64 * c + 8 * j);
                if (gid >= 2) pb[j] = 0u;
            }
            mbar_wait(bar_full + 8 * (12 + c), 0);
            if (tid == 0 && c == 0) TS(6);
            if (tid == 0 && c == 7) TS(8);
#pragma unroll
            for (int ks = 0; ks < 4; ks++) {
                uint32_t a0, a1, a2, a3;
                ldsm_x4_t(vbase + c * kSlotBytes + ks * 16 * 128, a0, a1, a2, a3);
                mma16816(oc[ks & 1], a0, a1, a2, a3, pb[2 * ks], pb[2 * ks + 1]);
            }
        }
        uint32_t* od = g_opart + (size_t)((g * kB + b) * 2 + half) * 272;
        float* stg = reinterpret_cast<float*>(sgen + OFF_STG) + warp * 32;
        if (tig == 0) {
            stg[gid] = oc[0][0] + oc[1][0];
            stg[16 + gid] = oc[0][1] + oc[1][1];
            stg[gid + 8] = oc[0][2] + oc[1][2];
            stg[16 + gid + 8] = oc[0][3] + oc[1][3];
        }
        __syncwarp();
        if (lane < 8) {
            const float4 v = *reinterpret_cast<const float4*>(stg + 4 * lane);
            st_word4v(od + (lane >> 2) * 128 + 16 * warp + 4 * (lane & 3), tagw(v.x, flag), tagw(v.y, flag),
                      tagw(v.z, flag), tagw(v.w, flag));
        } else if (warp == 0 && lane == 8) {
            float M0 = ml_s[0], L0 = ml_s[16], M1 = ml_s[8], L1 = ml_s[24];
#pragma unroll
            for (int w = 1; w < 8; w++) {
                M0 = fmaxf(M0, ml_s[w]);
                L0 += ml_s[16 + w];
                M1 = fmaxf(M1, ml_s[8 + w]);
                L1 += ml_s[24 + w];
            }
            st_word4v(od + 256, tagw(M0, flag), tagw(L0, flag), tagw(M1, flag), tagw(L1, flag));
        }
    }
    if (tid == 0) TS(13);

    {
        const int bb = tid >> 6, head = (tid >> 5) & 1, d4 = tid & 31;
        const uint32_t* src = g_opart + (size_t)((g * kB + bb) * 2) * 272;
        uint4 wa, wb2, sa, sb;
        if (tid == 0) TS(18);
        for (int it = 0; it < kSpinLimit; it++) {
            wa = ld_word4(src + head * 128 + 4 * d4);
            wb2 = ld_word4(src + 272 + head * 128 + 4 * d4);
            sa = ld_word4(src + 256);
            sb = ld_word4(src + 272 + 256);
            const uint32_t bad = (wa.x ^ flag) | (wa.y ^ flag) | (wa.z ^ flag) | (wa.w ^ flag) | (wb2.x ^ flag) |
                                 (wb2.y ^ flag) | (wb2.z ^ flag) | (wb2.w ^ flag) | (sa.x ^ flag) | (sa.y ^ flag) |
                                 (sa.z ^ flag) | (sa.w ^ flag) | (sb.x ^ flag) | (sb.y ^ flag) | (sb.z ^ flag) |
                                 (sb.w ^ flag);
            if (!(bad & 1u)) break;
        }
        if (tid == 0) TS(19);
        if (tid == 255) TS(20);
        const float m0 = __uint_as_float(head ? sa.z : sa.x), l0 = __uint_as_float(head ? sa.w : sa.y);
        const float m1 = __uint_as_float(head ? sb.z : sb.x), l1 = __uint_as_float(head ? sb.w : sb.y);
        const float MM = fmaxf(m0, m1);
        const float e0 = exp2f((m0 - MM) * 1.4426950408889634f), e1 = exp2f((m1 - MM) * 1.4426950408889634f);
        const float inv = 1.0f / (e0 * l0 + e1 * l1);
        const float f0 = e0 * inv, f1 = e1 * inv;
        uint2 pk;
        pk.x = pack_bf16(f0 * __uint_as_float(wa.x) + f1 * __uint_as_float(wb2.x),
                         f0 * __uint_as_float(wa.y) + f1 * __uint_as_float(wb2.y));
        pk.y = pack_bf16(f0 * __uint_as_float(wa.z) + f1 * __uint_as_float(wb2.z),
                         f0 * __uint_as_float(wa.w) + f1 * __uint_as_float(wb2.w));
        *reinterpret_cast<uint2*>(o_s + bb * 264 + head * 128 + 4 * d4) = pk;
    }
    asm volatile("bar.sync 3, 288;" ::: "memory");
    if (tid == 0) TS(9);
    {
        mbar_wait(bar_full + 8 * 20, 0);
        mbar_wait(bar_full + 8 * 21, 0);
        if (tid == 0) TS(11);
        for (int nt = 7 - warp; nt < 9; nt += 8) {
            float c[4];
            gemv3_tile<18, 296>(sbase + OFF_B, h_s, nt, lane, c);
            if (gid < 4)
                st_word2(g_fpart + (size_t)(((r * 9 + nt) * 2 + 1) * kGroups + g) * 32 + gid * 8 + 2 * tig,
                         tagw(c[0], flag), tagw(c[1], flag));
        }
        if (tid == 0) TS(12);
    }

    mbar_wait(bar_full + 8 * 22, 0);
    mbar_wait(bar_full + 8 * 23, 0);
    if (tid == 0) TS(14);

    {
        float c[4];
        gemv3_tile<16, 264>(sbase + OFF_A, o_s, warp, lane, c);
        if (gid < 4)
            st_word2(g_fpart + (size_t)(((r * 9 + warp) * 2 + 0) * kGroups + g) * 32 + gid * 8 + 2 * tig,
                     tagw(c[0], flag), tagw(c[1], flag));
    }
    if (tid == 0) TS(15);

    if (cta < kFinalCons && warp == 0) {
        const int gh = lane >> 4, which = (lane >> 3) & 1, bc = lane & 7;
        const uint32_t* src = g_fpart + (size_t)cta * 1024 + (which * kGroups + gh * 8) * 32 + bc * 4;
        uint4 w[8];
        for (int it = 0; it < kSpinLimit; it++) {
            uint32_t bad = 0;
#pragma unroll
            for (int i = 0; i < 8; i++) {
                w[i] = ld_word4(src + i * 32);
                bad |= (w[i].x ^ flag) | (w[i].y ^ flag) | (w[i].z ^ flag) | (w[i].w ^ flag);
            }
            if (!__any_sync(0xffffffffu, bad & 1u)) break;
        }
        if (tid == 0) TS(16);
        float v[4] = {0.f, 0.f, 0.f, 0.f};
#pragma unroll
        for (int i = 0; i < 8; i++) {
            v[0] += __uint_as_float(w[i].x);
            v[1] += __uint_as_float(w[i].y);
            v[2] += __uint_as_float(w[i].z);
            v[3] += __uint_as_float(w[i].w);
        }
        float gsum[4];
#pragma unroll
        for (int j = 0; j < 4; j++) {
            v[j] += __shfl_xor_sync(0xffffffffu, v[j], 16);
            gsum[j] = __shfl_xor_sync(0xffffffffu, v[j], 8);
        }
        if (lane < 8) {
            float o4[4];
#pragma unroll
            for (int j = 0; j < 4; j++) {
                const float gg = bfr(silu_f(bfr(gsum[j])));
                const float sg = bfr(bfr(v[j]) * gg);
                o4[j] = x_fin[j] + sg;
            }
            const int rc = cta / 9, ntc = cta - 9 * rc;
            uint2 pk;
            pk.x = pack_bf16(o4[0], o4[1]);
            pk.y = pack_bf16(o4[2], o4[3]);
            *reinterpret_cast<uint2*>(out + (lane >> 1) * kD + kCols3 * rc + 8 * ntc + (lane & 1) * 4) = pk;
        }
        if (tid == 0) TS(17);
        if (cta == 0 && tid == 0) {
            asm volatile("st.relaxed.gpu.global.u32 [%0], %1;" ::"l"(&g_epoch), "r"(epoch + 1u) : "memory");
        }
    }
}

typedef CUresult (*PFN_encodeTiled)(CUtensorMap*, CUtensorMapDataType, cuuint32_t, void*, const cuuint64_t*,
                                    const cuuint64_t*, const cuuint32_t*, const cuuint32_t*, CUtensorMapInterleave,
                                    CUtensorMapSwizzle, CUtensorMapL2promotion, CUtensorMapFloatOOBfill);

void make_map(PFN_encodeTiled enc, CUtensorMap* map, const void* ptr, uint64_t cols, uint64_t rows, uint32_t box_c,
              uint32_t box_r, CUtensorMapSwizzle swz, CUtensorMapL2promotion promo) {
    cuuint64_t gdim[2] = {cols, rows};
    cuuint64_t gstr[1] = {cols * 2};
    cuuint32_t box[2] = {box_c, box_r};
    cuuint32_t estr[2] = {1, 1};
    enc(map, CU_TENSOR_MAP_DATA_TYPE_BFLOAT16, 2, const_cast<void*>(ptr), gdim, gstr, box, estr,
        CU_TENSOR_MAP_INTERLEAVE_NONE, swz, promo, CU_TENSOR_MAP_FLOAT_OOB_FILL_NONE);
}

}

extern "C" void kernel_launch(void* const* d_in, const int* in_sizes, int n_in, void* d_out, int out_size) {
    (void)in_sizes;
    (void)n_in;
    (void)out_size;
    static PFN_encodeTiled enc = nullptr;
    if (!enc) {
        void* fn = nullptr;
        cudaDriverEntryPointQueryResult st;
        cudaGetDriverEntryPoint("cuTensorMapEncodeTiled", &fn, cudaEnableDefault, &st);
        enc = (PFN_encodeTiled)fn;
        cudaFuncSetAttribute(fused_decode_kernel, cudaFuncAttributeMaxDynamicSharedMemorySize, SMEM_BYTES);
    }
    CUtensorMap kmap, vmap, womap, w2map, wqmap, w1map;
    make_map(enc, &wqmap, d_in[3], kNQ, kD, 64, kRows1, CU_TENSOR_MAP_SWIZZLE_128B, CU_TENSOR_MAP_L2_PROMOTION_L2_256B);
    make_map(enc, &w1map, d_in[6], kF, kD, 72, kRows1, CU_TENSOR_MAP_SWIZZLE_NONE, CU_TENSOR_MAP_L2_PROMOTION_L2_256B);
    make_map(enc, &kmap, d_in[1], kDh, (uint64_t)kB * kHkv * kSk, 64, kChunkKeys, CU_TENSOR_MAP_SWIZZLE_128B,
             CU_TENSOR_MAP_L2_PROMOTION_L2_256B);
    make_map(enc, &vmap, d_in[2], kDh, (uint64_t)kB * kHkv * kSk, 64, kChunkKeys, CU_TENSOR_MAP_SWIZZLE_128B,
             CU_TENSOR_MAP_L2_PROMOTION_L2_256B);
    make_map(enc, &womap, d_in[4], kD, kNQ, kCols3, 128, CU_TENSOR_MAP_SWIZZLE_NONE,
             CU_TENSOR_MAP_L2_PROMOTION_L2_128B);
    make_map(enc, &w2map, d_in[7], kD, kF, kCols3, 144, CU_TENSOR_MAP_SWIZZLE_NONE,
             CU_TENSOR_MAP_L2_PROMOTION_L2_128B);
    fused_decode_kernel<<<kCTAs, 288, SMEM_BYTES>>>(kmap, vmap, womap, w2map, wqmap, w1map,
                                                    (const __nv_bfloat16*)d_in[0], (__nv_bfloat16*)d_out);
}
```

```cpp
#include <cuda_runtime.h>
#include <cuda_bf16.h>
#include <cuda.h>
#include <stdint.h>

namespace {

constexpr int kB = 4, kD = 576, kHkv = 16, kSk = 4096, kDh = 128, kWin = 1024, kF = 4608;
constexpr int kNQ = 4096;
constexpr int kGroups = 16, kRanks = 8, kCTAs = 128;
constexpr int kRows1 = 72;
constexpr int kQCols = 256, kHCols = 288;
constexpr int kCols3 = 72;
constexpr int kChunkKeys = 64;
constexpr int kFinalCons = 72;

constexpr int kSlotBytes = 16384;
constexpr int OFF_KV = 0;
constexpr int STR_W3 = 144;
constexpr int BOX_WQ = 144 * 64;
constexpr int BOX_W1 = 144 * 80;
constexpr int OFF_A = 8 * kSlotBytes;
constexpr int SZ_A = 4 * BOX_WQ;
constexpr int OFF_B = OFF_A + SZ_A;
constexpr int SZ_B = 4 * BOX_W1;
constexpr int OFF_XN = OFF_B + SZ_B;
constexpr int OFF_Q = OFF_XN + 4 * 584 * 2;
constexpr int OFF_H = OFF_Q + 544;
constexpr int OFF_O = OFF_H + 4 * 296 * 2;
constexpr int OFF_P = OFF_O + 4 * 264 * 2;
constexpr int OFF_ML = OFF_P + 2 * 520 * 2;
constexpr int OFF_STG = OFF_ML + 128;
constexpr int OFF_BAR = OFF_STG + 1024;
constexpr int SMEM_USED = OFF_BAR + 288;
constexpr int SMEM_BYTES = SMEM_USED + 1024;

static_assert(OFF_A % 128 == 0 && OFF_B % 128 == 0, "align");
static_assert(OFF_BAR % 8 == 0 && OFF_STG % 16 == 0, "align");
static_assert(SMEM_BYTES <= 232448, "smem");

__device__ __align__(128) uint32_t g_qx[kGroups * kB * kQCols];
__device__ __align__(128) uint32_t g_hx[kGroups * kB * kHCols];
__device__ __align__(128) uint32_t g_opart[kGroups * kB * 2 * 2 * 136];
__device__ __align__(128) uint32_t g_fpart[kFinalCons * 2 * kGroups * 32];
__device__ uint32_t g_epoch;

constexpr int kSpinLimit = 1 << 22;
#define KWINDOW 3
constexpr int kWindow = KWINDOW;

#define ORDER 2
#define G_FIRST (ORDER == 1 || ORDER == 2 || ORDER == 4)
__constant__ int c_order[24] = {0, 1, 2, 3, 4, 5, 6, 7, 8, 9, 10, 11, 20, 21, 12, 13, 14, 15, 16, 17, 18, 19, 22, 23};

#define TS(k)
#define TS2(k)

__device__ __forceinline__ uint32_t smem_u32(const void* p) {
    return (uint32_t)__cvta_generic_to_shared(p);
}
__device__ __forceinline__ void mbar_init(uint32_t bar, uint32_t count) {
    asm volatile("mbarrier.init.shared::cta.b64 [%0], %1;" ::"r"(bar), "r"(count) : "memory");
}
__device__ __forceinline__ void mbar_expect_tx(uint32_t bar, uint32_t bytes) {
    asm volatile("mbarrier.arrive.expect_tx.shared::cta.b64 _, [%0], %1;" ::"r"(bar), "r"(bytes) : "memory");
}
__device__ __forceinline__ void mbar_arrive(uint32_t bar) {
    asm volatile("mbarrier.arrive.shared::cta.b64 _, [%0];" ::"r"(bar) : "memory");
}
__device__ __forceinline__ bool mbar_try_wait(uint32_t bar, uint32_t parity) {
    uint32_t ok;
    asm volatile(
        "{\n .reg .pred p;\n mbarrier.try_wait.parity.shared::cta.b64 p, [%1], %2;\n selp.u32 %0, 1, 0, p;\n}"
        : "=r"(ok)
        : "r"(bar), "r"(parity)
        : "memory");
    return ok != 0;
}
__device__ __forceinline__ void mbar_wait(uint32_t bar, uint32_t parity) {
    for (int i = 0; i < kSpinLimit; i++) {
        if (mbar_try_wait(bar, parity)) break;
    }
}
__device__ __forceinline__ void bulk_g2s(uint32_t dst, const void* src, uint32_t bytes, uint32_t bar) {
    asm volatile(
        "cp.async.bulk.shared::cluster.global.mbarrier::complete_tx::bytes [%0], [%1], %2, [%3];" ::"r"(dst),
        "l"(src), "r"(bytes), "r"(bar)
        : "memory");
}
__device__ __forceinline__ void tma_2d_ef(uint32_t dst, const CUtensorMap* map, int c0, int c1, uint32_t bar) {
    uint64_t pol;
    asm volatile("createpolicy.fractional.L2::evict_first.b64 %0, 1.0;" : "=l"(pol));
    asm volatile(
        "cp.async.bulk.tensor.2d.shared::cluster.global.mbarrier::complete_tx::bytes.L2::cache_hint [%0], [%1, {%3, %4}], [%2], %5;" ::"r"(dst),
        "l"(map), "r"(bar), "r"(c0), "r"(c1), "l"(pol)
        : "memory");
}
__device__ __forceinline__ void tma_2d(uint32_t dst, const CUtensorMap* map, int c0, int c1, uint32_t bar) {
    asm volatile(
        "cp.async.bulk.tensor.2d.shared::cluster.global.mbarrier::complete_tx::bytes [%0], [%1, {%3, %4}], [%2];" ::"r"(dst),
        "l"(map), "r"(bar), "r"(c0), "r"(c1)
        : "memory");
}
__device__ __forceinline__ void ldsm_x4(uint32_t addr, uint32_t& r0, uint32_t& r1, uint32_t& r2, uint32_t& r3) {
    asm volatile("ldmatrix.sync.aligned.m8n8.x4.shared.b16 {%0,%1,%2,%3}, [%4];"
                 : "=r"(r0), "=r"(r1), "=r"(r2), "=r"(r3)
                 : "r"(addr)
                 : "memory");
}
__device__ __forceinline__ void ldsm_x4_t(uint32_t addr, uint32_t& r0, uint32_t& r1, uint32_t& r2, uint32_t& r3) {
    asm volatile("ldmatrix.sync.aligned.m8n8.x4.trans.shared.b16 {%0,%1,%2,%3}, [%4];"
                 : "=r"(r0), "=r"(r1), "=r"(r2), "=r"(r3)
                 : "r"(addr)
                 : "memory");
}
__device__ __forceinline__ void ldsm_x2_t(uint32_t addr, uint32_t& r0, uint32_t& r1) {
    asm volatile("ldmatrix.sync.aligned.m8n8.x2.trans.shared.b16 {%0,%1}, [%2];"
                 : "=r"(r0), "=r"(r1)
                 : "r"(addr)
                 : "memory");
}
__device__ __forceinline__ void mma16816(float (&c)[4], uint32_t a0, uint32_t a1, uint32_t a2, uint32_t a3,
                                         uint32_t b0, uint32_t b1) {
    asm volatile(
        "mma.sync.aligned.m16n8k16.row.col.f32.bf16.bf16.f32 {%0,%1,%2,%3}, {%4,%5,%6,%7}, {%8,%9}, {%0,%1,%2,%3};"
        : "+f"(c[0]), "+f"(c[1]), "+f"(c[2]), "+f"(c[3])
        : "r"(a0), "r"(a1), "r"(a2), "r"(a3), "r"(b0), "r"(b1));
}
__device__ __forceinline__ void mma1688(float (&c)[4], uint32_t a0, uint32_t a1, uint32_t b0) {
    asm volatile("mma.sync.aligned.m16n8k8.row.col.f32.bf16.bf16.f32 {%0,%1,%2,%3}, {%4,%5}, {%6}, {%0,%1,%2,%3};"
                 : "+f"(c[0]), "+f"(c[1]), "+f"(c[2]), "+f"(c[3])
                 : "r"(a0), "r"(a1), "r"(b0));
}
__device__ __forceinline__ void bar_cons() { asm volatile("bar.sync 1, 256;" ::: "memory"); }

__device__ __forceinline__ float bfr(float x) { return __bfloat162float(__float2bfloat16_rn(x)); }
__device__ __forceinline__ uint32_t pack_bf16(float lo, float hi) {
    __nv_bfloat162 v = __floats2bfloat162_rn(lo, hi);
    return *reinterpret_cast<uint32_t*>(&v);
}
__device__ __forceinline__ uint32_t tagw(float v, uint32_t flag) { return (__float_as_uint(v) & ~1u) | flag; }
__device__ __forceinline__ void st_word(uint32_t* p, uint32_t v) {
    asm volatile("st.relaxed.gpu.global.u32 [%0], %1;" ::"l"(p), "r"(v) : "memory");
}
__device__ __forceinline__ void st_word2(uint32_t* p, uint32_t v0, uint32_t v1) {
    asm volatile("st.relaxed.gpu.global.v2.u32 [%0], {%1,%2};" ::"l"(p), "r"(v0), "r"(v1) : "memory");
}
__device__ __forceinline__ void st_word4(uint32_t* p, uint32_t v) {
    asm volatile("st.relaxed.gpu.global.v4.u32 [%0], {%1,%1,%1,%1};" ::"l"(p), "r"(v) : "memory");
}
__device__ __forceinline__ void st_word4v(uint32_t* p, uint32_t a, uint32_t b, uint32_t c, uint32_t d) {
    asm volatile("st.relaxed.gpu.global.v4.u32 [%0], {%1,%2,%3,%4};" ::"l"(p), "r"(a), "r"(b), "r"(c), "r"(d) : "memory");
}
__device__ __forceinline__ uint32_t ld_word(const uint32_t* p) {
    uint32_t v;
    asm volatile("ld.relaxed.gpu.global.u32 %0, [%1];" : "=r"(v) : "l"(p) : "memory");
    return v;
}
__device__ __forceinline__ uint2 ld_word2(const uint32_t* p) {
    uint2 v;
    asm volatile("ld.relaxed.gpu.global.v2.u32 {%0,%1}, [%2];" : "=r"(v.x), "=r"(v.y) : "l"(p) : "memory");
    return v;
}
__device__ __forceinline__ uint4 ld_word4(const uint32_t* p) {
    uint4 v;
    asm volatile("ld.relaxed.gpu.global.v4.u32 {%0,%1,%2,%3}, [%4];"
                 : "=r"(v.x), "=r"(v.y), "=r"(v.z), "=r"(v.w)
                 : "l"(p)
                 : "memory");
    return v;
}
__device__ __forceinline__ float silu_f(float x) { return x / (1.0f + __expf(-x)); }

template <int KSTEPS, int ASTRIDE>
__device__ __forceinline__ void gemv3_tile(uint32_t wbuf, const __nv_bfloat16* act, int nt, int lane, float (&c)[4]) {
    const int gid = lane >> 2, tig = lane & 3, lm_i = lane & 7, lm_j = lane >> 3;
    const uint32_t wb = wbuf + (8 * lm_j + lm_i) * STR_W3 + nt * 16;
    const __nv_bfloat16* ap = act + (gid & 3) * ASTRIDE + 2 * tig;
    float acc[4][4];
#pragma unroll
    for (int i = 0; i < 4; i++) acc[i][0] = acc[i][1] = acc[i][2] = acc[i][3] = 0.f;
#pragma unroll
    for (int kk = 0; kk < KSTEPS / 2; kk++) {
        uint32_t b0, b1, b2, b3;
        ldsm_x4_t(wb + kk * 32 * STR_W3, b0, b1, b2, b3);
        uint32_t a0 = *reinterpret_cast<const uint32_t*>(ap + 32 * kk);
        uint32_t a2 = *reinterpret_cast<const uint32_t*>(ap + 32 * kk + 8);
        uint32_t a4 = *reinterpret_cast<const uint32_t*>(ap + 32 * kk + 16);
        uint32_t a6 = *reinterpret_cast<const uint32_t*>(ap + 32 * kk + 24);
        if (gid >= 4) a0 = a2 = a4 = a6 = 0u;
        mma16816(acc[(2 * kk) & 3], a0, 0u, a2, 0u, b0, b1);
        mma16816(acc[(2 * kk + 1) & 3], a4, 0u, a6, 0u, b2, b3);
    }
    c[0] = (acc[0][0] + acc[1][0]) + (acc[2][0] + acc[3][0]);
    c[1] = (acc[0][1] + acc[1][1]) + (acc[2][1] + acc[3][1]);
    c[2] = c[3] = 0.f;
}

__global__ void __launch_bounds__(288, 1)
fused_decode_kernel(const __grid_constant__ CUtensorMap kmap, const __grid_constant__ CUtensorMap vmap,
                    const __grid_constant__ CUtensorMap womap, const __grid_constant__ CUtensorMap w2map,
                    const __grid_constant__ CUtensorMap wqmap, const __grid_constant__ CUtensorMap w1map,
                    const __nv_bfloat16* __restrict__ x, __nv_bfloat16* __restrict__ out) {
    extern __shared__ uint8_t smem_raw[];
    const uint32_t raw_u32 = smem_u32(smem_raw);
    const uint32_t sbase = (raw_u32 + 1023u) & ~1023u;
    uint8_t* sgen = smem_raw + (sbase - raw_u32);

    const int tid = threadIdx.x, warp = tid >> 5, lane = tid & 31;
    const int cta = blockIdx.x;
    const int g = cta >> 3, r = cta & 7;
    const int b = r >> 1, half = r & 1;

    const uint32_t bar_full = sbase + OFF_BAR;
    const uint32_t bar_empty = sbase + OFF_BAR + 24 * 8;
    const uint32_t bar_s1 = sbase + OFF_BAR + 32 * 8;

    const int kv_row0 = (b * kHkv + g) * kSk + (kSk - kWin) + half * 512;
    const int hst = (36 * r) >> 3;
    const int hcnt = ((36 * (r + 1)) >> 3) - hst;

    if (warp == 8) {
        if (lane == 0) {
            TS(0);
            for (int i = 0; i < 32; i++) mbar_init(bar_full + 8 * i, 1);
            mbar_init(bar_s1, 8);
            asm volatile("fence.mbarrier_init.release.cluster;" ::: "memory");
            asm volatile("fence.proxy.async.shared::cta;" ::: "memory");
        }
        __syncwarp();
        asm volatile("bar.arrive 2, 288;" ::: "memory");
#pragma unroll 1
        for (int n = 0; n < 24; n++) {
            const int u = c_order[n];
            if (n >= kWindow) mbar_wait(bar_full + 8 * c_order[n - kWindow], 0);
            const uint32_t bar = bar_full + 8 * u;
            if (u < 2) {
                if (lane == 0) {
                    mbar_expect_tx(bar, 2 * BOX_WQ);
                    tma_2d(sbase + OFF_A + (2 * u) * BOX_WQ, &wqmap, kQCols * g + 32 * r, 144 * (2 * u), bar);
                    tma_2d(sbase + OFF_A + (2 * u + 1) * BOX_WQ, &wqmap, kQCols * g + 32 * r, 144 * (2 * u + 1), bar);
                }
            } else if (u < 4) {
                if (lane == 0) {
                    mbar_expect_tx(bar, 2 * BOX_W1);
                    tma_2d(sbase + OFF_B + (2 * u - 4) * BOX_W1, &w1map, kHCols * g + 8 * hst, 144 * (2 * u - 4), bar);
                    tma_2d(sbase + OFF_B + (2 * u - 3) * BOX_W1, &w1map, kHCols * g + 8 * hst, 144 * (2 * u - 3), bar);
                }
            } else if (u < 20) {
                const int c = (u - 4) & 7;
                if (u >= 12) mbar_wait(bar_empty + 8 * c, 0);
                if (lane == 0) {
                    const CUtensorMap* mp = u >= 12 ? &vmap : &kmap;
                    mbar_expect_tx(bar, kSlotBytes);
                    tma_2d_ef(sbase + OFF_KV + c * kSlotBytes, mp, 0, kv_row0 + kChunkKeys * c, bar);
                    tma_2d_ef(sbase + OFF_KV + c * kSlotBytes + 8192, mp, 64, kv_row0 + kChunkKeys * c, bar);
                }
            } else if (u < 22) {
                mbar_wait(bar_s1, 0);
                if (lane == 0) {
                    mbar_expect_tx(bar, 144 * STR_W3);
                    tma_2d(sbase + OFF_B + (u - 20) * 144 * STR_W3, &w2map, kCols3 * r, kHCols * g + 144 * (u - 20), bar);
                }
            } else {
                mbar_wait(bar_s1, 0);
                if (lane == 0) {
                    mbar_expect_tx(bar, 128 * STR_W3);
                    tma_2d(sbase + OFF_A + (u - 22) * 128 * STR_W3, &womap, kCols3 * r, kQCols * g + 128 * (u - 22), bar);
                }
            }
            if (lane == 0) TS2(n);
            __syncwarp();
        }
        asm volatile("bar.sync 3, 288;" ::: "memory");
        mbar_wait(bar_full + 8 * 22, 0);
        mbar_wait(bar_full + 8 * 23, 0);
        const uint32_t flag_p = *reinterpret_cast<volatile uint32_t*>(sgen + OFF_BAR + 280);
        {
            float c[4];
            gemv3_tile<16, 264>(sbase + OFF_A, reinterpret_cast<const __nv_bfloat16*>(sgen + OFF_O), 8, lane, c);
            if ((lane >> 2) < 4)
                st_word2(g_fpart + (size_t)(((r * 9 + 8) * 2 + 0) * kGroups + g) * 32 + (lane >> 2) * 8 + 2 * (lane & 3),
                         tagw(c[0], flag_p), tagw(c[1], flag_p));
        }
        return;
    }

    uint32_t epoch;
    asm volatile("ld.relaxed.gpu.global.u32 %0, [%1];" : "=r"(epoch) : "l"(&g_epoch) : "memory");
    uint32_t xw[9];
    if (warp < 4) {
        const uint32_t* xr = reinterpret_cast<const uint32_t*>(x + warp * kD);
#pragma unroll
        for (int i = 0; i < 9; i++) xw[i] = __ldg(xr + lane + 32 * i);
    }
    float x_fin[4] = {0.f, 0.f, 0.f, 0.f};
    if (cta < kFinalCons && tid < 8) {
        const int rc = cta / 9, ntc = cta - 9 * rc;
        const uint2 xv = __ldg(reinterpret_cast<const uint2*>(x + (tid >> 1) * kD + kCols3 * rc + 8 * ntc + (tid & 1) * 4));
        x_fin[0] = __uint_as_float(xv.x << 16);
        x_fin[1] = __uint_as_float(xv.x & 0xffff0000u);
        x_fin[2] = __uint_as_float(xv.y << 16);
        x_fin[3] = __uint_as_float(xv.y & 0xffff0000u);
    }
    const uint32_t flag = (epoch + 1u) & 1u;

    __nv_bfloat16* xn_s = reinterpret_cast<__nv_bfloat16*>(sgen + OFF_XN);
    __nv_bfloat16* q_s = reinterpret_cast<__nv_bfloat16*>(sgen + OFF_Q);
    __nv_bfloat16* h_s = reinterpret_cast<__nv_bfloat16*>(sgen + OFF_H);
    __nv_bfloat16* o_s = reinterpret_cast<__nv_bfloat16*>(sgen + OFF_O);
    __nv_bfloat16* p_s = reinterpret_cast<__nv_bfloat16*>(sgen + OFF_P);
    float* ml_s = reinterpret_cast<float*>(sgen + OFF_ML);

    if (tid == 0) *reinterpret_cast<volatile uint32_t*>(sgen + OFF_BAR + 280) = flag;
    {
        const uint32_t inv = flag ^ 1u;
        if (tid < 32) {
            st_word4(g_qx + (size_t)(g * kB + (tid >> 3)) * kQCols + 32 * r + 4 * (tid & 7), inv);
        } else if (tid < 32 + 40) {
            const int i = tid - 32, bb = i / 10, c4 = i - bb * 10;
            if (c4 < 2 * hcnt) st_word4(g_hx + (size_t)(g * kB + bb) * kHCols + 8 * hst + 4 * c4, inv);
        } else if (tid >= 96 && tid < 96 + 68) {
            st_word4(g_opart + (size_t)((g * kB + b) * 2 + half) * 272 + 4 * (tid - 96), inv);
        } else if (tid >= 184) {
            const int i = tid - 184;
            const int nt = i >> 3, c4 = i & 7;
            st_word4(g_fpart + (size_t)(((r * 9 + nt) * 2 + 0) * kGroups + g) * 32 + 4 * c4, inv);
        }
    }

    if (warp < 4) {
        float v[18];
        float sum = 0.f;
#pragma unroll
        for (int i = 0; i < 9; i++) {
            v[2 * i] = __uint_as_float(xw[i] << 16);
            v[2 * i + 1] = __uint_as_float(xw[i] & 0xffff0000u);
            sum += v[2 * i] + v[2 * i + 1];
        }
#pragma unroll
        for (int o = 16; o > 0; o >>= 1) sum += __shfl_xor_sync(0xffffffffu, sum, o);
        const float mean = sum * (1.0f / kD);
        float sq = 0.f;
#pragma unroll
        for (int i = 0; i < 18; i++) {
            float d = v[i] - mean;
            sq += d * d;
        }
#pragma unroll
        for (int o = 16; o > 0; o >>= 1) sq += __shfl_xor_sync(0xffffffffu, sq, o);
        const float m_bf = bfr(mean);
        const float v_bf = bfr(sq * (1.0f / kD));
        const float den = bfr(sqrtf(bfr(v_bf + 1e-5f)));
#pragma unroll
        for (int i = 0; i < 9; i++) {
            const float a0 = bfr(v[2 * i] - m_bf) / den;
            const float a1 = bfr(v[2 * i + 1] - m_bf) / den;
            *reinterpret_cast<uint32_t*>(xn_s + warp * 584 + 2 * (lane + 32 * i)) = pack_bf16(a0, a1);
        }
    }
    asm volatile("bar.sync 2, 288;" ::: "memory");
    if (tid == 0) TS(1);

    const int gid = lane >> 2, tig = lane & 3;
    const int lm_i = lane & 7, lm_j = lane >> 3;

    {
        const __nv_bfloat16* ap = xn_s + (gid & 3) * 584 + 2 * tig;
#pragma unroll 1
        for (int job = warp; job < 9; job += 8) {
            const bool isq = job < 4;
            const int nt = isq ? job : job - 4;
            if (!isq && nt >= hcnt) break;
            float acc[4][4];
#pragma unroll
            for (int i = 0; i < 4; i++) acc[i][0] = acc[i][1] = acc[i][2] = acc[i][3] = 0.f;
#pragma unroll 1
            for (int bx = 0; bx < 4; bx++) {
                if ((bx & 1) == 0) mbar_wait(bar_full + 8 * ((isq ? 0 : 2) + (bx >> 1)), 0);
#pragma unroll
                for (int kk = 0; kk < 5; kk++) {
                    const int row = 32 * kk + 8 * lm_j + lm_i;
                    uint32_t addr;
                    if (isq)
                        addr = sbase + OFF_A + bx * BOX_WQ + row * 64 + ((nt ^ ((row >> 1) & 3)) << 4);
                    else
                        addr = sbase + OFF_B + bx * BOX_W1 + row * 80 + nt * 16;
                    const int k0 = 144 * bx + 32 * kk;
                    uint32_t a0 = *reinterpret_cast<const uint32_t*>(ap + k0);
                    uint32_t a2 = *reinterpret_cast<const uint32_t*>(ap + k0 + 8);
                    if (gid >= 4) a0 = a2 = 0u;
                    if (kk < 4) {
                        uint32_t b0, b1, b2, b3;
                        ldsm_x4_t(addr, b0, b1, b2, b3);
                        uint32_t a4 = *reinterpret_cast<const uint32_t*>(ap + k0 + 16);
                        uint32_t a6 = *reinterpret_cast<const uint32_t*>(ap + k0 + 24);
                        if (gid >= 4) a4 = a6 = 0u;
                        mma16816(acc[(2 * kk) & 3], a0, 0u, a2, 0u, b0, b1);
                        mma16816(acc[(2 * kk + 1) & 3], a4, 0u, a6, 0u, b2, b3);
                    } else {
                        uint32_t b0, b1;
                        ldsm_x2_t(addr, b0, b1);
                        mma16816(acc[0], a0, 0u, a2, 0u, b0, b1);
                    }
                }
            }
            float c0 = (acc[0][0] + acc[1][0]) + (acc[2][0] + acc[3][0]);
            float c1 = (acc[0][1] + acc[1][1]) + (acc[2][1] + acc[3][1]);
            if (gid < 4) {
                if (isq) {
                    const uint32_t pk = pack_bf16(c0, c1);
                    st_word2(g_qx + (size_t)(g * kB + gid) * kQCols + 32 * r + 8 * nt + 2 * tig, (pk << 16) | flag,
                             (pk & 0xffff0000u) | flag);
                } else {
                    const uint32_t pk = pack_bf16(silu_f(bfr(c0)), silu_f(bfr(c1)));
                    st_word2(g_hx + (size_t)(g * kB + gid) * kHCols + 8 * (hst + nt) + 2 * tig, (pk << 16) | flag,
                             (pk & 0xffff0000u) | flag);
                }
            }
        }
        if (tid == 0) TS(3);
    }
    __syncwarp();
    if (lane == 0) mbar_arrive(bar_s1);

    if (tid < 64) {
        const uint32_t* src = g_qx + (size_t)(g * kB + b) * kQCols + 4 * tid;
        uint4 w;
        for (int it = 0; it < kSpinLimit; it++) {
            w = ld_word4(src);
            const uint32_t bad = (w.x ^ flag) | (w.y ^ flag) | (w.z ^ flag) | (w.w ^ flag);
            if (!(bad & 1u)) break;
        }
        uint2 pk;
        pk.x = (w.x >> 16) | (w.y & 0xffff0000u);
        pk.y = (w.z >> 16) | (w.w & 0xffff0000u);
        *reinterpret_cast<uint2*>(q_s + (tid >> 5) * 136 + 4 * (tid & 31)) = pk;
    }
    bar_cons();
    if (tid == 0) TS(4);

    float sc[8][2];
    {
        const uint32_t slot = sbase + OFF_KV + warp * kSlotBytes;
        uint32_t qa[16];
#pragma unroll
        for (int j = 0; j < 8; j++) {
            qa[2 * j] = gid < 2 ? *reinterpret_cast<const uint32_t*>(q_s + gid * 136 + 16 * j + 2 * tig) : 0u;
            qa[2 * j + 1] = gid < 2 ? *reinterpret_cast<const uint32_t*>(q_s + gid * 136 + 16 * j + 8 + 2 * tig) : 0u;
        }
        mbar_wait(bar_full + 8 * (4 + warp), 0);
        if (tid == 0) TS(5);
        if (tid == 224) TS(7);
        float mx = -INFINITY;
        const float scale = 0.08838834764831845f;
#pragma unroll
        for (int nt = 0; nt < 8; nt++) {
            float acc[4] = {0.f, 0.f, 0.f, 0.f};
#pragma unroll
            for (int kk = 0; kk < 4; kk++) {
                const int cg = 4 * kk + lm_j;
                const uint32_t addr =
                    slot + (cg >> 3) * 8192 + (8 * nt + lm_i) * 128 + (((cg & 7) ^ lm_i) << 4);
                uint32_t b0, b1, b2, b3;
                ldsm_x4(addr, b0, b1, b2, b3);
                mma16816(acc, qa[4 * kk], 0u, qa[4 * kk + 1], 0u, b0, b1);
                mma16816(acc, qa[4 * kk + 2], 0u, qa[4 * kk + 3], 0u, b2, b3);
            }
            sc[nt][0] = bfr(bfr(acc[0]) * scale);
            sc[nt][1] = bfr(bfr(acc[1]) * scale);
            mx = fmaxf(mx, fmaxf(sc[nt][0], sc[nt][1]));
        }
        __syncwarp();
        if (lane == 0) mbar_arrive(bar_empty + 8 * warp);
        mx = fmaxf(mx, __shfl_xor_sync(0xffffffffu, mx, 1));
        mx = fmaxf(mx, __shfl_xor_sync(0xffffffffu, mx, 2));
        if (lane == 0 || lane == 4) ml_s[(lane >> 2) * 8 + warp] = mx;
    }

    {
        for (int idx = tid; idx < kB * kHCols / 4; idx += 256) {
            const uint32_t* src = g_hx + (size_t)g * kB * kHCols + 4 * idx;
            uint4 w;
            for (int it = 0; it < kSpinLimit; it++) {
                w = ld_word4(src);
                const uint32_t bad = (w.x ^ flag) | (w.y ^ flag) | (w.z ^ flag) | (w.w ^ flag);
                if (!(bad & 1u)) break;
            }
            const int bb = idx / 72, c4 = idx - bb * 72;
            uint2 pk;
            pk.x = (w.x >> 16) | (w.y & 0xffff0000u);
            pk.y = (w.z >> 16) | (w.w & 0xffff0000u);
            *reinterpret_cast<uint2*>(h_s + bb * 296 + 4 * c4) = pk;
        }
        if (tid == 0) TS(10);
    }
    bar_cons();

    {
        const int hh = gid & 1;
        float M = ml_s[hh * 8];
#pragma unroll
        for (int w = 1; w < 8; w++) M = fmaxf(M, ml_s[hh * 8 + w]);
        const float l2e = 1.4426950408889634f;
        float lsum = 0.f;
#pragma unroll
        for (int nt = 0; nt < 8; nt++) {
            const float p0 = exp2f((sc[nt][0] - M) * l2e);
            const float p1 = exp2f((sc[nt][1] - M) * l2e);
            lsum += p0 + p1;
            if (gid < 2) *reinterpret_cast<uint32_t*>(p_s + gid * 520 + 64 * warp + 8 * nt + 2 * tig) = pack_bf16(p0, p1);
        }
        lsum += __shfl_xor_sync(0xffffffffu, lsum, 1);
        lsum += __shfl_xor_sync(0xffffffffu, lsum, 2);
        if (lane == 0 || lane == 4) ml_s[16 + (lane >> 2) * 8 + warp] = lsum;
    }
    bar_cons();

    {
        float oc[2][4] = {{0.f, 0.f, 0.f, 0.f}, {0.f, 0.f, 0.f, 0.f}};
        const int cg = 2 * warp + (lm_j & 1);
        const uint32_t vbase = sbase + OFF_KV + (cg >> 3) * 8192 + ((lm_j >> 1) * 8 + lm_i) * 128 + (((cg & 7) ^ lm_i) << 4);
        const __nv_bfloat16* pp = p_s + (gid & 1) * 520 + 2 * tig;
#pragma unroll 1
        for (int c = 0; c < 8; c++) {
            uint32_t pb[8];
#pragma unroll
            for (int j = 0; j < 8; j++) {
                pb[j] = *reinterpret_cast<const uint32_t*>(pp + 64 * c + 8 * j);
                if (gid >= 2) pb[j] = 0u;
            }
            if (c == 3) {
                mbar_wait(bar_full + 8 * 20, 0);
                mbar_wait(bar_full + 8 * 21, 0);
                for (int nt = 7 - warp; nt < 9; nt += 8) {
                    float cc[4];
                    gemv3_tile<18, 296>(sbase + OFF_B, h_s, nt, lane, cc);
                    if (gid < 4)
                        st_word2(g_fpart + (size_t)(((r * 9 + nt) * 2 + 1) * kGroups + g) * 32 + gid * 8 + 2 * tig,
                                 tagw(cc[0], flag), tagw(cc[1], flag));
                }
            }
            mbar_wait(bar_full + 8 * (12 + c), 0);
            if (tid == 0 && c == 0) TS(6);
            if (tid == 0 && c == 7) TS(8);
#pragma unroll
            for (int ks = 0; ks < 4; ks++) {
                uint32_t a0, a1, a2, a3;
                ldsm_x4_t(vbase + c * kSlotBytes + ks * 16 * 128, a0, a1, a2, a3);
                mma16816(oc[ks & 1], a0, a1, a2, a3, pb[2 * ks], pb[2 * ks + 1]);
            }
        }
        uint32_t* od = g_opart + (size_t)((g * kB + b) * 2 + half) * 272;
        float* stg = reinterpret_cast<float*>(sgen + OFF_STG) + warp * 32;
        if (tig == 0) {
            stg[gid] = oc[0][0] + oc[1][0];
            stg[16 + gid] = oc[0][1] + oc[1][1];
            stg[gid + 8] = oc[0][2] + oc[1][2];
            stg[16 + gid + 8] = oc[0][3] + oc[1][3];
        }
        __syncwarp();
        if (lane < 8) {
            const float4 v = *reinterpret_cast<const float4*>(stg + 4 * lane);
            st_word4v(od + (lane >> 2) * 128 + 16 * warp + 4 * (lane & 3), tagw(v.x, flag), tagw(v.y, flag),
                      tagw(v.z, flag), tagw(v.w, flag));
        } else if (warp == 0 && lane == 8) {
            float M0 = ml_s[0], L0 = ml_s[16], M1 = ml_s[8], L1 = ml_s[24];
#pragma unroll
            for (int w = 1; w < 8; w++) {
                M0 = fmaxf(M0, ml_s[w]);
                L0 += ml_s[16 + w];
                M1 = fmaxf(M1, ml_s[8 + w]);
                L1 += ml_s[24 + w];
            }
            st_word4v(od + 256, tagw(M0, flag), tagw(L0, flag), tagw(M1, flag), tagw(L1, flag));
        }
    }
    if (tid == 0) TS(13);

    {
        const int bb = tid >> 6, head = (tid >> 5) & 1, d4 = tid & 31;
        const uint32_t* src = g_opart + (size_t)((g * kB + bb) * 2) * 272;
        uint4 wa, wb2, sa, sb;
        if (tid == 0) TS(18);
        for (int it = 0; it < kSpinLimit; it++) {
            wa = ld_word4(src + head * 128 + 4 * d4);
            wb2 = ld_word4(src + 272 + head * 128 + 4 * d4);
            sa = ld_word4(src + 256);
            sb = ld_word4(src + 272 + 256);
            const uint32_t bad = (wa.x ^ flag) | (wa.y ^ flag) | (wa.z ^ flag) | (wa.w ^ flag) | (wb2.x ^ flag) |
                                 (wb2.y ^ flag) | (wb2.z ^ flag) | (wb2.w ^ flag) | (sa.x ^ flag) | (sa.y ^ flag) |
                                 (sa.z ^ flag) | (sa.w ^ flag) | (sb.x ^ flag) | (sb.y ^ flag) | (sb.z ^ flag) |
                                 (sb.w ^ flag);
            if (!(bad & 1u)) break;
        }
        if (tid == 0) TS(19);
        if (tid == 255) TS(20);
        const float m0 = __uint_as_float(head ? sa.z : sa.x), l0 = __uint_as_float(head ? sa.w : sa.y);
        const float m1 = __uint_as_float(head ? sb.z : sb.x), l1 = __uint_as_float(head ? sb.w : sb.y);
        const float MM = fmaxf(m0, m1);
        const float e0 = exp2f((m0 - MM) * 1.4426950408889634f), e1 = exp2f((m1 - MM) * 1.4426950408889634f);
        const float inv = 1.0f / (e0 * l0 + e1 * l1);
        const float f0 = e0 * inv, f1 = e1 * inv;
        uint2 pk;
        pk.x = pack_bf16(f0 * __uint_as_float(wa.x) + f1 * __uint_as_float(wb2.x),
                         f0 * __uint_as_float(wa.y) + f1 * __uint_as_float(wb2.y));
        pk.y = pack_bf16(f0 * __uint_as_float(wa.z) + f1 * __uint_as_float(wb2.z),
                         f0 * __uint_as_float(wa.w) + f1 * __uint_as_float(wb2.w));
        *reinterpret_cast<uint2*>(o_s + bb * 264 + head * 128 + 4 * d4) = pk;
    }
    asm volatile("bar.sync 3, 288;" ::: "memory");
    if (tid == 0) TS(9);
    mbar_wait(bar_full + 8 * 22, 0);
    mbar_wait(bar_full + 8 * 23, 0);
    if (tid == 0) TS(14);

    {
        float c[4];
        gemv3_tile<16, 264>(sbase + OFF_A, o_s, warp, lane, c);
        if (gid < 4)
            st_word2(g_fpart + (size_t)(((r * 9 + warp) * 2 + 0) * kGroups + g) * 32 + gid * 8 + 2 * tig,
                     tagw(c[0], flag), tagw(c[1], flag));
    }
    if (tid == 0) TS(15);

    if (cta < kFinalCons && warp == 0) {
        const int gh = lane >> 4, which = (lane >> 3) & 1, bc = lane & 7;
        const uint32_t* src = g_fpart + (size_t)cta * 1024 + (which * kGroups + gh * 8) * 32 + bc * 4;
        uint4 w[8];
        for (int it = 0; it < kSpinLimit; it++) {
            uint32_t bad = 0;
#pragma unroll
            for (int i = 0; i < 8; i++) {
                w[i] = ld_word4(src + i * 32);
                bad |= (w[i].x ^ flag) | (w[i].y ^ flag) | (w[i].z ^ flag) | (w[i].w ^ flag);
            }
            if (!__any_sync(0xffffffffu, bad & 1u)) break;
        }
        if (tid == 0) TS(16);
        float v[4] = {0.f, 0.f, 0.f, 0.f};
#pragma unroll
        for (int i = 0; i < 8; i++) {
            v[0] += __uint_as_float(w[i].x);
            v[1] += __uint_as_float(w[i].y);
            v[2] += __uint_as_float(w[i].z);
            v[3] += __uint_as_float(w[i].w);
        }
        float gsum[4];
#pragma unroll
        for (int j = 0; j < 4; j++) {
            v[j] += __shfl_xor_sync(0xffffffffu, v[j], 16);
            gsum[j] = __shfl_xor_sync(0xffffffffu, v[j], 8);
        }
        if (lane < 8) {
            float o4[4];
#pragma unroll
            for (int j = 0; j < 4; j++) {
                const float gg = bfr(silu_f(bfr(gsum[j])));
                const float sg = bfr(bfr(v[j]) * gg);
                o4[j] = x_fin[j] + sg;
            }
            const int rc = cta / 9, ntc = cta - 9 * rc;
            uint2 pk;
            pk.x = pack_bf16(o4[0], o4[1]);
            pk.y = pack_bf16(o4[2], o4[3]);
            *reinterpret_cast<uint2*>(out + (lane >> 1) * kD + kCols3 * rc + 8 * ntc + (lane & 1) * 4) = pk;
        }
        if (tid == 0) TS(17);
        if (cta == 0 && tid == 0) {
            asm volatile("st.relaxed.gpu.global.u32 [%0], %1;" ::"l"(&g_epoch), "r"(epoch + 1u) : "memory");
        }
    }
}

typedef CUresult (*PFN_encodeTiled)(CUtensorMap*, CUtensorMapDataType, cuuint32_t, void*, const cuuint64_t*,
                                    const cuuint64_t*, const cuuint32_t*, const cuuint32_t*, CUtensorMapInterleave,
                                    CUtensorMapSwizzle, CUtensorMapL2promotion, CUtensorMapFloatOOBfill);

void make_map(PFN_encodeTiled enc, CUtensorMap* map, const void* ptr, uint64_t cols, uint64_t rows, uint32_t box_c,
              uint32_t box_r, CUtensorMapSwizzle swz, CUtensorMapL2promotion promo) {
    cuuint64_t gdim[2] = {cols, rows};
    cuuint64_t gstr[1] = {cols * 2};
    cuuint32_t box[2] = {box_c, box_r};
    cuuint32_t estr[2] = {1, 1};
    enc(map, CU_TENSOR_MAP_DATA_TYPE_BFLOAT16, 2, const_cast<void*>(ptr), gdim, gstr, box, estr,
        CU_TENSOR_MAP_INTERLEAVE_NONE, swz, promo, CU_TENSOR_MAP_FLOAT_OOB_FILL_NONE);
}

}

extern "C" void kernel_launch(void* const* d_in, const int* in_sizes, int n_in, void* d_out, int out_size) {
    (void)in_sizes;
    (void)n_in;
    (void)out_size;
    static PFN_encodeTiled enc = nullptr;
    if (!enc) {
        void* fn = nullptr;
        cudaDriverEntryPointQueryResult st;
        cudaGetDriverEntryPoint("cuTensorMapEncodeTiled", &fn, cudaEnableDefault, &st);
        enc = (PFN_encodeTiled)fn;
        cudaFuncSetAttribute(fused_decode_kernel, cudaFuncAttributeMaxDynamicSharedMemorySize, SMEM_BYTES);
    }
    CUtensorMap kmap, vmap, womap, w2map, wqmap, w1map;
    make_map(enc, &wqmap, d_in[3], kNQ, kD, 32, 144, CU_TENSOR_MAP_SWIZZLE_64B, CU_TENSOR_MAP_L2_PROMOTION_L2_128B);
    make_map(enc, &w1map, d_in[6], kF, kD, 40, 144, CU_TENSOR_MAP_SWIZZLE_NONE, CU_TENSOR_MAP_L2_PROMOTION_L2_128B);
    make_map(enc, &kmap, d_in[1], kDh, (uint64_t)kB * kHkv * kSk, 64, kChunkKeys, CU_TENSOR_MAP_SWIZZLE_128B,
             CU_TENSOR_MAP_L2_PROMOTION_L2_256B);
    make_map(enc, &vmap, d_in[2], kDh, (uint64_t)kB * kHkv * kSk, 64, kChunkKeys, CU_TENSOR_MAP_SWIZZLE_128B,
             CU_TENSOR_MAP_L2_PROMOTION_L2_256B);
    make_map(enc, &womap, d_in[4], kD, kNQ, kCols3, 128, CU_TENSOR_MAP_SWIZZLE_NONE,
             CU_TENSOR_MAP_L2_PROMOTION_L2_128B);
    make_map(enc, &w2map, d_in[7], kD, kF, kCols3, 144, CU_TENSOR_MAP_SWIZZLE_NONE,
             CU_TENSOR_MAP_L2_PROMOTION_L2_128B);
    fused_decode_kernel<<<kCTAs, 288, SMEM_BYTES>>>(kmap, vmap, womap, w2map, wqmap, w1map,
                                                    (const __nv_bfloat16*)d_in[0], (__nv_bfloat16*)d_out);
}
```

```cpp
#include <cuda_runtime.h>
#include <cuda_bf16.h>
#include <cuda.h>
#include <stdint.h>

namespace {

constexpr int kB = 4, kD = 576, kHkv = 16, kSk = 4096, kDh = 128, kWin = 1024, kF = 4608;
constexpr int kNQ = 4096;
constexpr int kGroups = 16, kRanks = 8, kCTAs = 128;
constexpr int kRows1 = 72;
constexpr int kQCols = 256, kHCols = 288;
constexpr int kCols3 = 72;
constexpr int kChunkKeys = 64;
constexpr int kFinalCons = 72;

constexpr int kSlotBytes = 16384;
constexpr int OFF_KV = 0;
constexpr int STR_W3 = 144;
constexpr int BOX_WQ = 144 * 64;
constexpr int BOX_W1 = 144 * 80;
constexpr int OFF_A = 8 * kSlotBytes;
constexpr int SZ_A = 4 * BOX_WQ;
constexpr int OFF_B = OFF_A + SZ_A;
constexpr int SZ_B = 4 * BOX_W1;
constexpr int OFF_XN = OFF_B + SZ_B;
constexpr int OFF_Q = OFF_XN + 4 * 584 * 2;
constexpr int OFF_H = OFF_Q + 544;
constexpr int OFF_O = OFF_H + 4 * 296 * 2;
constexpr int OFF_P = OFF_O + 4 * 264 * 2;
constexpr int OFF_ML = OFF_P + 2 * 520 * 2;
constexpr int OFF_STG = OFF_ML + 128;
constexpr int OFF_BAR = OFF_STG + 1024;
constexpr int SMEM_USED = OFF_BAR + 288;
constexpr int SMEM_BYTES = SMEM_USED + 1024;

static_assert(OFF_A % 128 == 0 && OFF_B % 128 == 0, "align");
static_assert(OFF_BAR % 8 == 0 && OFF_STG % 16 == 0, "align");
static_assert(SMEM_BYTES <= 232448, "smem");

__device__ __align__(128) uint32_t g_qx[kGroups * kB * kQCols];
__device__ __align__(128) uint32_t g_hx[kGroups * kB * kHCols];
__device__ __align__(128) uint32_t g_opart[kGroups * kB * 2 * 2 * 136];
__device__ __align__(128) uint32_t g_fpart[kFinalCons * 2 * kGroups * 32];
__device__ uint32_t g_epoch;

constexpr int kSpinLimit = 1 << 22;
#define KWINDOW 3
constexpr int kWindow = KWINDOW;

#define ORDER 2
#define G_FIRST (ORDER == 1 || ORDER == 2 || ORDER == 4)
__constant__ int c_order[24] = {0, 1, 2, 3, 4, 5, 6, 7, 8, 9, 10, 11, 20, 21, 12, 13, 14, 15, 16, 17, 18, 19, 22, 23};

#define TS(k)
#define TS2(k)

__device__ __forceinline__ uint32_t smem_u32(const void* p) {
    return (uint32_t)__cvta_generic_to_shared(p);
}
__device__ __forceinline__ void mbar_init(uint32_t bar, uint32_t count) {
    asm volatile("mbarrier.init.shared::cta.b64 [%0], %1;" ::"r"(bar), "r"(count) : "memory");
}
__device__ __forceinline__ void mbar_expect_tx(uint32_t bar, uint32_t bytes) {
    asm volatile("mbarrier.arrive.expect_tx.shared::cta.b64 _, [%0], %1;" ::"r"(bar), "r"(bytes) : "memory");
}
__device__ __forceinline__ void mbar_arrive(uint32_t bar) {
    asm volatile("mbarrier.arrive.shared::cta.b64 _, [%0];" ::"r"(bar) : "memory");
}
__device__ __forceinline__ bool mbar_try_wait(uint32_t bar, uint32_t parity) {
    uint32_t ok;
    asm volatile(
        "{\n .reg .pred p;\n mbarrier.try_wait.parity.shared::cta.b64 p, [%1], %2;\n selp.u32 %0, 1, 0, p;\n}"
        : "=r"(ok)
        : "r"(bar), "r"(parity)
        : "memory");
    return ok != 0;
}
__device__ __forceinline__ void mbar_wait(uint32_t bar, uint32_t parity) {
    for (int i = 0; i < kSpinLimit; i++) {
        if (mbar_try_wait(bar, parity)) break;
    }
}
__device__ __forceinline__ void bulk_g2s(uint32_t dst, const void* src, uint32_t bytes, uint32_t bar) {
    asm volatile(
        "cp.async.bulk.shared::cluster.global.mbarrier::complete_tx::bytes [%0], [%1], %2, [%3];" ::"r"(dst),
        "l"(src), "r"(bytes), "r"(bar)
        : "memory");
}
__device__ __forceinline__ void tma_2d_ef(uint32_t dst, const CUtensorMap* map, int c0, int c1, uint32_t bar) {
    uint64_t pol;
    asm volatile("createpolicy.fractional.L2::evict_first.b64 %0, 1.0;" : "=l"(pol));
    asm volatile(
        "cp.async.bulk.tensor.2d.shared::cluster.global.mbarrier::complete_tx::bytes.L2::cache_hint [%0], [%1, {%3, %4}], [%2], %5;" ::"r"(dst),
        "l"(map), "r"(bar), "r"(c0), "r"(c1), "l"(pol)
        : "memory");
}
__device__ __forceinline__ void tma_2d(uint32_t dst, const CUtensorMap* map, int c0, int c1, uint32_t bar) {
    asm volatile(
        "cp.async.bulk.tensor.2d.shared::cluster.global.mbarrier::complete_tx::bytes [%0], [%1, {%3, %4}], [%2];" ::"r"(dst),
        "l"(map), "r"(bar), "r"(c0), "r"(c1)
        : "memory");
}
__device__ __forceinline__ void ldsm_x4(uint32_t addr, uint32_t& r0, uint32_t& r1, uint32_t& r2, uint32_t& r3) {
    asm volatile("ldmatrix.sync.aligned.m8n8.x4.shared.b16 {%0,%1,%2,%3}, [%4];"
                 : "=r"(r0), "=r"(r1), "=r"(r2), "=r"(r3)
                 : "r"(addr)
                 : "memory");
}
__device__ __forceinline__ void ldsm_x4_t(uint32_t addr, uint32_t& r0, uint32_t& r1, uint32_t& r2, uint32_t& r3) {
    asm volatile("ldmatrix.sync.aligned.m8n8.x4.trans.shared.b16 {%0,%1,%2,%3}, [%4];"
                 : "=r"(r0), "=r"(r1), "=r"(r2), "=r"(r3)
                 : "r"(addr)
                 : "memory");
}
__device__ __forceinline__ void ldsm_x2_t(uint32_t addr, uint32_t& r0, uint32_t& r1) {
    asm volatile("ldmatrix.sync.aligned.m8n8.x2.trans.shared.b16 {%0,%1}, [%2];"
                 : "=r"(r0), "=r"(r1)
                 : "r"(addr)
                 : "memory");
}
__device__ __forceinline__ void mma16816(float (&c)[4], uint32_t a0, uint32_t a1, uint32_t a2, uint32_t a3,
                                         uint32_t b0, uint32_t b1) {
    asm volatile(
        "mma.sync.aligned.m16n8k16.row.col.f32.bf16.bf16.f32 {%0,%1,%2,%3}, {%4,%5,%6,%7}, {%8,%9}, {%0,%1,%2,%3};"
        : "+f"(c[0]), "+f"(c[1]), "+f"(c[2]), "+f"(c[3])
        : "r"(a0), "r"(a1), "r"(a2), "r"(a3), "r"(b0), "r"(b1));
}
__device__ __forceinline__ void mma1688(float (&c)[4], uint32_t a0, uint32_t a1, uint32_t b0) {
    asm volatile("mma.sync.aligned.m16n8k8.row.col.f32.bf16.bf16.f32 {%0,%1,%2,%3}, {%4,%5}, {%6}, {%0,%1,%2,%3};"
                 : "+f"(c[0]), "+f"(c[1]), "+f"(c[2]), "+f"(c[3])
                 : "r"(a0), "r"(a1), "r"(b0));
}
__device__ __forceinline__ void bar_cons() { asm volatile("bar.sync 1, 256;" ::: "memory"); }

__device__ __forceinline__ float bfr(float x) { return __bfloat162float(__float2bfloat16_rn(x)); }
__device__ __forceinline__ uint32_t pack_bf16(float lo, float hi) {
    __nv_bfloat162 v = __floats2bfloat162_rn(lo, hi);
    return *reinterpret_cast<uint32_t*>(&v);
}
__device__ __forceinline__ uint32_t tagw(float v, uint32_t flag) { return (__float_as_uint(v) & ~1u) | flag; }
__device__ __forceinline__ void st_word(uint32_t* p, uint32_t v) {
    asm volatile("st.relaxed.gpu.global.u32 [%0], %1;" ::"l"(p), "r"(v) : "memory");
}
__device__ __forceinline__ void st_word2(uint32_t* p, uint32_t v0, uint32_t v1) {
    asm volatile("st.relaxed.gpu.global.v2.u32 [%0], {%1,%2};" ::"l"(p), "r"(v0), "r"(v1) : "memory");
}
__device__ __forceinline__ void st_word4(uint32_t* p, uint32_t v) {
    asm volatile("st.relaxed.gpu.global.v4.u32 [%0], {%1,%1,%1,%1};" ::"l"(p), "r"(v) : "memory");
}
__device__ __forceinline__ void st_word4v(uint32_t* p, uint32_t a, uint32_t b, uint32_t c, uint32_t d) {
    asm volatile("st.relaxed.gpu.global.v4.u32 [%0], {%1,%2,%3,%4};" ::"l"(p), "r"(a), "r"(b), "r"(c), "r"(d) : "memory");
}
__device__ __forceinline__ uint32_t ld_word(const uint32_t* p) {
    uint32_t v;
    asm volatile("ld.relaxed.gpu.global.u32 %0, [%1];" : "=r"(v) : "l"(p) : "memory");
    return v;
}
__device__ __forceinline__ uint2 ld_word2(const uint32_t* p) {
    uint2 v;
    asm volatile("ld.relaxed.gpu.global.v2.u32 {%0,%1}, [%2];" : "=r"(v.x), "=r"(v.y) : "l"(p) : "memory");
    return v;
}
__device__ __forceinline__ uint4 ld_word4(const uint32_t* p) {
    uint4 v;
    asm volatile("ld.relaxed.gpu.global.v4.u32 {%0,%1,%2,%3}, [%4];"
                 : "=r"(v.x), "=r"(v.y), "=r"(v.z), "=r"(v.w)
                 : "l"(p)
                 : "memory");
    return v;
}
__device__ __forceinline__ float silu_f(float x) { return x / (1.0f + __expf(-x)); }

template <int KSTEPS, int ASTRIDE>
__device__ __forceinline__ void gemv3_tile(uint32_t wbuf, const __nv_bfloat16* act, int nt, int lane, float (&c)[4]) {
    const int gid = lane >> 2, tig = lane & 3, lm_i = lane & 7, lm_j = lane >> 3;
    const uint32_t wb = wbuf + (8 * lm_j + lm_i) * STR_W3 + nt * 16;
    const __nv_bfloat16* ap = act + (gid & 3) * ASTRIDE + 2 * tig;
    float acc[4][4];
#pragma unroll
    for (int i = 0; i < 4; i++) acc[i][0] = acc[i][1] = acc[i][2] = acc[i][3] = 0.f;
#pragma unroll
    for (int kk = 0; kk < KSTEPS / 2; kk++) {
        uint32_t b0, b1, b2, b3;
        ldsm_x4_t(wb + kk * 32 * STR_W3, b0, b1, b2, b3);
        uint32_t a0 = *reinterpret_cast<const uint32_t*>(ap + 32 * kk);
        uint32_t a2 = *reinterpret_cast<const uint32_t*>(ap + 32 * kk + 8);
        uint32_t a4 = *reinterpret_cast<const uint32_t*>(ap + 32 * kk + 16);
        uint32_t a6 = *reinterpret_cast<const uint32_t*>(ap + 32 * kk + 24);
        if (gid >= 4) a0 = a2 = a4 = a6 = 0u;
        mma16816(acc[(2 * kk) & 3], a0, 0u, a2, 0u, b0, b1);
        mma16816(acc[(2 * kk + 1) & 3], a4, 0u, a6, 0u, b2, b3);
    }
    c[0] = (acc[0][0] + acc[1][0]) + (acc[2][0] + acc[3][0]);
    c[1] = (acc[0][1] + acc[1][1]) + (acc[2][1] + acc[3][1]);
    c[2] = c[3] = 0.f;
}

__global__ void __launch_bounds__(288, 1)
fused_decode_kernel(const __grid_constant__ CUtensorMap kmap, const __grid_constant__ CUtensorMap vmap,
                    const __grid_constant__ CUtensorMap womap, const __grid_constant__ CUtensorMap w2map,
                    const __grid_constant__ CUtensorMap wqmap, const __grid_constant__ CUtensorMap w1map,
                    const __nv_bfloat16* __restrict__ x, __nv_bfloat16* __restrict__ out) {
    extern __shared__ uint8_t smem_raw[];
    const uint32_t raw_u32 = smem_u32(smem_raw);
    const uint32_t sbase = (raw_u32 + 1023u) & ~1023u;
    uint8_t* sgen = smem_raw + (sbase - raw_u32);

    const int tid = threadIdx.x, warp = tid >> 5, lane = tid & 31;
    const int cta = blockIdx.x;
    const int g = cta >> 3, r = cta & 7;
    const int b = r >> 1, half = r & 1;

    const uint32_t bar_full = sbase + OFF_BAR;
    const uint32_t bar_empty = sbase + OFF_BAR + 24 * 8;
    const uint32_t bar_s1 = sbase + OFF_BAR + 32 * 8;

    const int kv_row0 = (b * kHkv + g) * kSk + (kSk - kWin) + half * 512;
    const int hst = (36 * r) >> 3;
    const int hcnt = ((36 * (r + 1)) >> 3) - hst;

    if (warp == 8) {
        if (lane == 0) {
            TS(0);
            for (int i = 0; i < 32; i++) mbar_init(bar_full + 8 * i, 1);
            mbar_init(bar_s1, 8);
            asm volatile("fence.mbarrier_init.release.cluster;" ::: "memory");
            asm volatile("fence.proxy.async.shared::cta;" ::: "memory");
        }
        __syncwarp();
        asm volatile("bar.arrive 2, 288;" ::: "memory");
#pragma unroll 1
        for (int n = 0; n < 24; n++) {
            const int u = c_order[n];
            if (n >= kWindow) mbar_wait(bar_full + 8 * c_order[n - kWindow], 0);
            const uint32_t bar = bar_full + 8 * u;
            if (u < 2) {
                if (lane == 0) {
                    mbar_expect_tx(bar, 2 * BOX_WQ);
                    tma_2d(sbase + OFF_A + (2 * u) * BOX_WQ, &wqmap, kQCols * g + 32 * r, 144 * (2 * u), bar);
                    tma_2d(sbase + OFF_A + (2 * u + 1) * BOX_WQ, &wqmap, kQCols * g + 32 * r, 144 * (2 * u + 1), bar);
                }
            } else if (u < 4) {
                if (lane == 0) {
                    mbar_expect_tx(bar, 2 * BOX_W1);
                    tma_2d(sbase + OFF_B + (2 * u - 4) * BOX_W1, &w1map, kHCols * g + 8 * hst, 144 * (2 * u - 4), bar);
                    tma_2d(sbase + OFF_B + (2 * u - 3) * BOX_W1, &w1map, kHCols * g + 8 * hst, 144 * (2 * u - 3), bar);
                }
            } else if (u < 20) {
                const int c = (u - 4) & 7;
                if (u >= 12) mbar_wait(bar_empty + 8 * c, 0);
                if (lane == 0) {
                    const CUtensorMap* mp = u >= 12 ? &vmap : &kmap;
                    mbar_expect_tx(bar, kSlotBytes);
                    tma_2d_ef(sbase + OFF_KV + c * kSlotBytes, mp, 0, kv_row0 + kChunkKeys * c, bar);
                    tma_2d_ef(sbase + OFF_KV + c * kSlotBytes + 8192, mp, 64, kv_row0 + kChunkKeys * c, bar);
                }
            } else if (u < 22) {
                mbar_wait(bar_s1, 0);
                if (lane == 0) {
                    mbar_expect_tx(bar, 144 * STR_W3);
                    tma_2d(sbase + OFF_B + (u - 20) * 144 * STR_W3, &w2map, kCols3 * r, kHCols * g + 144 * (u - 20), bar);
                }
            } else {
                mbar_wait(bar_s1, 0);
                if (lane == 0) {
                    mbar_expect_tx(bar, 128 * STR_W3);
                    tma_2d(sbase + OFF_A + (u - 22) * 128 * STR_W3, &womap, kCols3 * r, kQCols * g + 128 * (u - 22), bar);
                }
            }
            if (lane == 0) TS2(n);
            __syncwarp();
        }
        asm volatile("bar.sync 3, 288;" ::: "memory");
        mbar_wait(bar_full + 8 * 22, 0);
        mbar_wait(bar_full + 8 * 23, 0);
        const uint32_t flag_p = *reinterpret_cast<volatile uint32_t*>(sgen + OFF_BAR + 280);
        {
            float c[4];
            gemv3_tile<16, 264>(sbase + OFF_A, reinterpret_cast<const __nv_bfloat16*>(sgen + OFF_O), 8, lane, c);
            if ((lane >> 2) < 4)
                st_word2(g_fpart + (size_t)(((r * 9 + 8) * 2 + 0) * kGroups + g) * 32 + (lane >> 2) * 8 + 2 * (lane & 3),
                         tagw(c[0], flag_p), tagw(c[1], flag_p));
        }
        return;
    }

    uint32_t epoch;
    asm volatile("ld.relaxed.gpu.global.u32 %0, [%1];" : "=r"(epoch) : "l"(&g_epoch) : "memory");
    uint32_t xw[9];
    if (warp < 4) {
        const uint32_t* xr = reinterpret_cast<const uint32_t*>(x + warp * kD);
#pragma unroll
        for (int i = 0; i < 9; i++) xw[i] = __ldg(xr + lane + 32 * i);
    }
    float x_fin[4] = {0.f, 0.f, 0.f, 0.f};
    if (cta < kFinalCons && tid < 8) {
        const int rc = cta / 9, ntc = cta - 9 * rc;
        const uint2 xv = __ldg(reinterpret_cast<const uint2*>(x + (tid >> 1) * kD + kCols3 * rc + 8 * ntc + (tid & 1) * 4));
        x_fin[0] = __uint_as_float(xv.x << 16);
        x_fin[1] = __uint_as_float(xv.x & 0xffff0000u);
        x_fin[2] = __uint_as_float(xv.y << 16);
        x_fin[3] = __uint_as_float(xv.y & 0xffff0000u);
    }
    const uint32_t flag = (epoch + 1u) & 1u;

    __nv_bfloat16* xn_s = reinterpret_cast<__nv_bfloat16*>(sgen + OFF_XN);
    __nv_bfloat16* q_s = reinterpret_cast<__nv_bfloat16*>(sgen + OFF_Q);
    __nv_bfloat16* h_s = reinterpret_cast<__nv_bfloat16*>(sgen + OFF_H);
    __nv_bfloat16* o_s = reinterpret_cast<__nv_bfloat16*>(sgen + OFF_O);
    __nv_bfloat16* p_s = reinterpret_cast<__nv_bfloat16*>(sgen + OFF_P);
    float* ml_s = reinterpret_cast<float*>(sgen + OFF_ML);

    if (tid == 0) *reinterpret_cast<volatile uint32_t*>(sgen + OFF_BAR + 280) = flag;
    {
        const uint32_t inv = flag ^ 1u;
        if (tid < 32) {
            st_word4(g_qx + (size_t)(g * kB + (tid >> 3)) * kQCols + 32 * r + 4 * (tid & 7), inv);
        } else if (tid < 32 + 40) {
            {
            const int i = tid - 32, bb = i / 10, c4 = i - bb * 10;
            if (c4 < 2 * hcnt) st_word4(g_hx + (size_t)(g * kB + bb) * kHCols + 8 * hst + 4 * c4, inv);
            }
        } else if (tid >= 96 && tid < 96 + 68) {
            st_word4(g_opart + (size_t)((g * kB + b) * 2 + half) * 272 + 4 * (tid - 96), inv);
        } else if (tid >= 184) {
            const int i = tid - 184;
            const int nt = i >> 3, c4 = i & 7;
            st_word4(g_fpart + (size_t)(((r * 9 + nt) * 2 + 0) * kGroups + g) * 32 + 4 * c4, inv);
        }
    }

    if (warp < 4) {
        float v[18];
        float sum = 0.f;
#pragma unroll
        for (int i = 0; i < 9; i++) {
            v[2 * i] = __uint_as_float(xw[i] << 16);
            v[2 * i + 1] = __uint_as_float(xw[i] & 0xffff0000u);
            sum += v[2 * i] + v[2 * i + 1];
        }
#pragma unroll
        for (int o = 16; o > 0; o >>= 1) sum += __shfl_xor_sync(0xffffffffu, sum, o);
        const float mean = sum * (1.0f / kD);
        float sq = 0.f;
#pragma unroll
        for (int i = 0; i < 18; i++) {
            float d = v[i] - mean;
            sq += d * d;
        }
#pragma unroll
        for (int o = 16; o > 0; o >>= 1) sq += __shfl_xor_sync(0xffffffffu, sq, o);
        const float m_bf = bfr(mean);
        const float v_bf = bfr(sq * (1.0f / kD));
        const float den = bfr(sqrtf(bfr(v_bf + 1e-5f)));
#pragma unroll
        for (int i = 0; i < 9; i++) {
            const float a0 = bfr(v[2 * i] - m_bf) / den;
            const float a1 = bfr(v[2 * i + 1] - m_bf) / den;
            *reinterpret_cast<uint32_t*>(xn_s + warp * 584 + 2 * (lane + 32 * i)) = pack_bf16(a0, a1);
        }
    }
    asm volatile("bar.sync 2, 288;" ::: "memory");
    if (tid == 0) TS(1);

    const int gid = lane >> 2, tig = lane & 3;
    const int lm_i = lane & 7, lm_j = lane >> 3;

    {
        const __nv_bfloat16* ap = xn_s + (gid & 3) * 584 + 2 * tig;
#pragma unroll 1
        for (int job = warp; job < 9; job += 8) {
            const bool isq = job < 4;
            const int nt = isq ? job : job - 4;
            if (!isq && nt >= hcnt) break;
            float acc[4][4];
#pragma unroll
            for (int i = 0; i < 4; i++) acc[i][0] = acc[i][1] = acc[i][2] = acc[i][3] = 0.f;
#pragma unroll 1
            for (int bx = 0; bx < 4; bx++) {
                if ((bx & 1) == 0) mbar_wait(bar_full + 8 * ((isq ? 0 : 2) + (bx >> 1)), 0);
#pragma unroll
                for (int kk = 0; kk < 5; kk++) {
                    const int row = 32 * kk + 8 * lm_j + lm_i;
                    uint32_t addr;
                    if (isq)
                        addr = sbase + OFF_A + bx * BOX_WQ + row * 64 + ((nt ^ ((row >> 1) & 3)) << 4);
                    else
                        addr = sbase + OFF_B + bx * BOX_W1 + row * 80 + nt * 16;
                    const int k0 = 144 * bx + 32 * kk;
                    uint32_t a0 = *reinterpret_cast<const uint32_t*>(ap + k0);
                    uint32_t a2 = *reinterpret_cast<const uint32_t*>(ap + k0 + 8);
                    if (gid >= 4) a0 = a2 = 0u;
                    if (kk < 4) {
                        uint32_t b0, b1, b2, b3;
                        ldsm_x4_t(addr, b0, b1, b2, b3);
                        uint32_t a4 = *reinterpret_cast<const uint32_t*>(ap + k0 + 16);
                        uint32_t a6 = *reinterpret_cast<const uint32_t*>(ap + k0 + 24);
                        if (gid >= 4) a4 = a6 = 0u;
                        mma16816(acc[(2 * kk) & 3], a0, 0u, a2, 0u, b0, b1);
                        mma16816(acc[(2 * kk + 1) & 3], a4, 0u, a6, 0u, b2, b3);
                    } else {
                        uint32_t b0, b1;
                        ldsm_x2_t(addr, b0, b1);
                        mma16816(acc[0], a0, 0u, a2, 0u, b0, b1);
                    }
                }
            }
            float c0 = (acc[0][0] + acc[1][0]) + (acc[2][0] + acc[3][0]);
            float c1 = (acc[0][1] + acc[1][1]) + (acc[2][1] + acc[3][1]);
            if (gid < 4) {
                if (isq) {
                    const uint32_t pk = pack_bf16(c0, c1);
                    st_word2(g_qx + (size_t)(g * kB + gid) * kQCols + 32 * r + 8 * nt + 2 * tig, (pk << 16) | flag,
                             (pk & 0xffff0000u) | flag);
                } else {
                    const uint32_t pk = pack_bf16(silu_f(bfr(c0)), silu_f(bfr(c1)));
                    st_word2(g_hx + (size_t)(g * kB + gid) * kHCols + 8 * (hst + nt) + 2 * tig, (pk << 16) | flag,
                             (pk & 0xffff0000u) | flag);
                }
            }
        }
        if (tid == 0) TS(3);
    }
    __syncwarp();
    if (lane == 0) mbar_arrive(bar_s1);

    if (tid < 64) {
        const uint32_t* src = g_qx + (size_t)(g * kB + b) * kQCols + 4 * tid;
        uint4 w;
        for (int it = 0; it < kSpinLimit; it++) {
            w = ld_word4(src);
            const uint32_t bad = (w.x ^ flag) | (w.y ^ flag) | (w.z ^ flag) | (w.w ^ flag);
            if (!(bad & 1u)) break;
        }
        uint2 pk;
        pk.x = (w.x >> 16) | (w.y & 0xffff0000u);
        pk.y = (w.z >> 16) | (w.w & 0xffff0000u);
        *reinterpret_cast<uint2*>(q_s + (tid >> 5) * 136 + 4 * (tid & 31)) = pk;
    }
    bar_cons();
    if (tid == 0) TS(4);

    float sc[8][2];
    {
        const uint32_t slot = sbase + OFF_KV + warp * kSlotBytes;
        uint32_t qa[16];
#pragma unroll
        for (int j = 0; j < 8; j++) {
            qa[2 * j] = gid < 2 ? *reinterpret_cast<const uint32_t*>(q_s + gid * 136 + 16 * j + 2 * tig) : 0u;
            qa[2 * j + 1] = gid < 2 ? *reinterpret_cast<const uint32_t*>(q_s + gid * 136 + 16 * j + 8 + 2 * tig) : 0u;
        }
        mbar_wait(bar_full + 8 * (4 + warp), 0);
        if (tid == 0) TS(5);
        if (tid == 224) TS(7);
        float mx = -INFINITY;
        const float scale = 0.08838834764831845f;
#pragma unroll
        for (int nt = 0; nt < 8; nt++) {
            float acc[4] = {0.f, 0.f, 0.f, 0.f};
#pragma unroll
            for (int kk = 0; kk < 4; kk++) {
                const int cg = 4 * kk + lm_j;
                const uint32_t addr =
                    slot + (cg >> 3) * 8192 + (8 * nt + lm_i) * 128 + (((cg & 7) ^ lm_i) << 4);
                uint32_t b0, b1, b2, b3;
                ldsm_x4(addr, b0, b1, b2, b3);
                mma16816(acc, qa[4 * kk], 0u, qa[4 * kk + 1], 0u, b0, b1);
                mma16816(acc, qa[4 * kk + 2], 0u, qa[4 * kk + 3], 0u, b2, b3);
            }
            sc[nt][0] = bfr(bfr(acc[0]) * scale);
            sc[nt][1] = bfr(bfr(acc[1]) * scale);
            mx = fmaxf(mx, fmaxf(sc[nt][0], sc[nt][1]));
        }
        __syncwarp();
        if (lane == 0) mbar_arrive(bar_empty + 8 * warp);
        mx = fmaxf(mx, __shfl_xor_sync(0xffffffffu, mx, 1));
        mx = fmaxf(mx, __shfl_xor_sync(0xffffffffu, mx, 2));
        if (lane == 0 || lane == 4) ml_s[(lane >> 2) * 8 + warp] = mx;
    }

    {
        for (int idx = tid; idx < kB * kHCols / 4; idx += 256) {
            const uint32_t* src = g_hx + (size_t)g * kB * kHCols + 4 * idx;
            uint4 w;
            for (int it = 0; it < kSpinLimit; it++) {
                w = ld_word4(src);
                const uint32_t bad = (w.x ^ flag) | (w.y ^ flag) | (w.z ^ flag) | (w.w ^ flag);
                if (!(bad & 1u)) break;
            }
            const int bb = idx / 72, c4 = idx - bb * 72;
            uint2 pk;
            pk.x = (w.x >> 16) | (w.y & 0xffff0000u);
            pk.y = (w.z >> 16) | (w.w & 0xffff0000u);
            *reinterpret_cast<uint2*>(h_s + bb * 296 + 4 * c4) = pk;
        }
        if (tid == 0) TS(10);
    }
    bar_cons();

    {
        const int hh = gid & 1;
        float M = ml_s[hh * 8];
#pragma unroll
        for (int w = 1; w < 8; w++) M = fmaxf(M, ml_s[hh * 8 + w]);
        const float l2e = 1.4426950408889634f;
        float lsum = 0.f;
#pragma unroll
        for (int nt = 0; nt < 8; nt++) {
            const float p0 = exp2f((sc[nt][0] - M) * l2e);
            const float p1 = exp2f((sc[nt][1] - M) * l2e);
            lsum += p0 + p1;
            if (gid < 2) *reinterpret_cast<uint32_t*>(p_s + gid * 520 + 64 * warp + 8 * nt + 2 * tig) = pack_bf16(p0, p1);
        }
        lsum += __shfl_xor_sync(0xffffffffu, lsum, 1);
        lsum += __shfl_xor_sync(0xffffffffu, lsum, 2);
        if (lane == 0 || lane == 4) ml_s[16 + (lane >> 2) * 8 + warp] = lsum;
    }
    bar_cons();

    {
        float oc[2][4] = {{0.f, 0.f, 0.f, 0.f}, {0.f, 0.f, 0.f, 0.f}};
        const int cg = 2 * warp + (lm_j & 1);
        const uint32_t vbase = sbase + OFF_KV + (cg >> 3) * 8192 + ((lm_j >> 1) * 8 + lm_i) * 128 + (((cg & 7) ^ lm_i) << 4);
        const __nv_bfloat16* pp = p_s + (gid & 1) * 520 + 2 * tig;
#pragma unroll 1
        for (int c = 0; c < 8; c++) {
            uint32_t pb[8];
#pragma unroll
            for (int j = 0; j < 8; j++) {
                pb[j] = *reinterpret_cast<const uint32_t*>(pp + 64 * c + 8 * j);
                if (gid >= 2) pb[j] = 0u;
            }
            if (c == 3) {
                mbar_wait(bar_full + 8 * 20, 0);
                mbar_wait(bar_full + 8 * 21, 0);
                for (int nt = 7 - warp; nt < 9; nt += 8) {
                    float cc[4];
                    gemv3_tile<18, 296>(sbase + OFF_B, h_s, nt, lane, cc);
                    if (gid < 4)
                        st_word2(g_fpart + (size_t)(((r * 9 + nt) * 2 + 1) * kGroups + g) * 32 + gid * 8 + 2 * tig,
                                 tagw(cc[0], flag), tagw(cc[1], flag));
                }
            }
            mbar_wait(bar_full + 8 * (12 + c), 0);
            if (tid == 0 && c == 0) TS(6);
            if (tid == 0 && c == 7) TS(8);
#pragma unroll
            for (int ks = 0; ks < 4; ks++) {
                uint32_t a0, a1, a2, a3;
                ldsm_x4_t(vbase + c * kSlotBytes + ks * 16 * 128, a0, a1, a2, a3);
                mma16816(oc[ks & 1], a0, a1, a2, a3, pb[2 * ks], pb[2 * ks + 1]);
            }
        }
        uint32_t* od = g_opart + (size_t)((g * kB + b) * 2 + half) * 272;
        float* stg = reinterpret_cast<float*>(sgen + OFF_STG) + warp * 32;
        if (tig == 0) {
            stg[gid] = oc[0][0] + oc[1][0];
            stg[16 + gid] = oc[0][1] + oc[1][1];
            stg[gid + 8] = oc[0][2] + oc[1][2];
            stg[16 + gid + 8] = oc[0][3] + oc[1][3];
        }
        __syncwarp();
        if (lane < 8) {
            const float4 v = *reinterpret_cast<const float4*>(stg + 4 * lane);
            st_word4v(od + (lane >> 2) * 128 + 16 * warp + 4 * (lane & 3), tagw(v.x, flag), tagw(v.y, flag),
                      tagw(v.z, flag), tagw(v.w, flag));
        } else if (warp == 0 && lane == 8) {
            float M0 = ml_s[0], L0 = ml_s[16], M1 = ml_s[8], L1 = ml_s[24];
#pragma unroll
            for (int w = 1; w < 8; w++) {
                M0 = fmaxf(M0, ml_s[w]);
                L0 += ml_s[16 + w];
                M1 = fmaxf(M1, ml_s[8 + w]);
                L1 += ml_s[24 + w];
            }
            st_word4v(od + 256, tagw(M0, flag), tagw(L0, flag), tagw(M1, flag), tagw(L1, flag));
        }
    }
    if (tid == 0) TS(13);

    {
        const int bb = tid >> 6, head = (tid >> 5) & 1, d4 = tid & 31;
        const uint32_t* src = g_opart + (size_t)((g * kB + bb) * 2) * 272;
        uint4 wa, wb2, sa, sb;
        if (tid == 0) TS(18);
        for (int it = 0; it < kSpinLimit; it++) {
            wa = ld_word4(src + head * 128 + 4 * d4);
            wb2 = ld_word4(src + 272 + head * 128 + 4 * d4);
            sa = ld_word4(src + 256);
            sb = ld_word4(src + 272 + 256);
            const uint32_t bad = (wa.x ^ flag) | (wa.y ^ flag) | (wa.z ^ flag) | (wa.w ^ flag) | (wb2.x ^ flag) |
                                 (wb2.y ^ flag) | (wb2.z ^ flag) | (wb2.w ^ flag) | (sa.x ^ flag) | (sa.y ^ flag) |
                                 (sa.z ^ flag) | (sa.w ^ flag) | (sb.x ^ flag) | (sb.y ^ flag) | (sb.z ^ flag) |
                                 (sb.w ^ flag);
            if (!(bad & 1u)) break;
        }
        if (tid == 0) TS(19);
        if (tid == 255) TS(20);
        const float m0 = __uint_as_float(head ? sa.z : sa.x), l0 = __uint_as_float(head ? sa.w : sa.y);
        const float m1 = __uint_as_float(head ? sb.z : sb.x), l1 = __uint_as_float(head ? sb.w : sb.y);
        const float MM = fmaxf(m0, m1);
        const float e0 = exp2f((m0 - MM) * 1.4426950408889634f), e1 = exp2f((m1 - MM) * 1.4426950408889634f);
        const float inv = 1.0f / (e0 * l0 + e1 * l1);
        const float f0 = e0 * inv, f1 = e1 * inv;
        uint2 pk;
        pk.x = pack_bf16(f0 * __uint_as_float(wa.x) + f1 * __uint_as_float(wb2.x),
                         f0 * __uint_as_float(wa.y) + f1 * __uint_as_float(wb2.y));
        pk.y = pack_bf16(f0 * __uint_as_float(wa.z) + f1 * __uint_as_float(wb2.z),
                         f0 * __uint_as_float(wa.w) + f1 * __uint_as_float(wb2.w));
        *reinterpret_cast<uint2*>(o_s + bb * 264 + head * 128 + 4 * d4) = pk;
    }
    asm volatile("bar.sync 3, 288;" ::: "memory");
    if (tid == 0) TS(9);
    float gate[4] = {0.f, 0.f, 0.f, 0.f};
    if (cta < kFinalCons && warp == 0) {
        const uint32_t* src = g_fpart + (size_t)cta * 1024 + 512 + (lane >> 3) * 4 * 32 + (lane & 7) * 4;
        uint4 w[4];
        for (int it = 0; it < kSpinLimit; it++) {
            uint32_t bad = 0;
#pragma unroll
            for (int i = 0; i < 4; i++) {
                w[i] = ld_word4(src + i * 32);
                bad |= (w[i].x ^ flag) | (w[i].y ^ flag) | (w[i].z ^ flag) | (w[i].w ^ flag);
            }
            if (!__any_sync(0xffffffffu, bad & 1u)) break;
        }
        gate[0] = (__uint_as_float(w[0].x) + __uint_as_float(w[1].x)) + (__uint_as_float(w[2].x) + __uint_as_float(w[3].x));
        gate[1] = (__uint_as_float(w[0].y) + __uint_as_float(w[1].y)) + (__uint_as_float(w[2].y) + __uint_as_float(w[3].y));
        gate[2] = (__uint_as_float(w[0].z) + __uint_as_float(w[1].z)) + (__uint_as_float(w[2].z) + __uint_as_float(w[3].z));
        gate[3] = (__uint_as_float(w[0].w) + __uint_as_float(w[1].w)) + (__uint_as_float(w[2].w) + __uint_as_float(w[3].w));
#pragma unroll
        for (int j = 0; j < 4; j++) {
            gate[j] += __shfl_xor_sync(0xffffffffu, gate[j], 8);
            gate[j] += __shfl_xor_sync(0xffffffffu, gate[j], 16);
            gate[j] = bfr(silu_f(bfr(gate[j])));
        }
    }
    mbar_wait(bar_full + 8 * 22, 0);
    mbar_wait(bar_full + 8 * 23, 0);
    if (tid == 0) TS(14);

    {
        float c[4];
        gemv3_tile<16, 264>(sbase + OFF_A, o_s, warp, lane, c);
        if (gid < 4)
            st_word2(g_fpart + (size_t)(((r * 9 + warp) * 2 + 0) * kGroups + g) * 32 + gid * 8 + 2 * tig,
                     tagw(c[0], flag), tagw(c[1], flag));
    }
    if (tid == 0) TS(15);

    if (cta < kFinalCons && warp == 0) {
        const uint32_t* src = g_fpart + (size_t)cta * 1024 + (lane >> 3) * 4 * 32 + (lane & 7) * 4;
        uint4 w[4];
        for (int it = 0; it < kSpinLimit; it++) {
            uint32_t bad = 0;
#pragma unroll
            for (int i = 0; i < 4; i++) {
                w[i] = ld_word4(src + i * 32);
                bad |= (w[i].x ^ flag) | (w[i].y ^ flag) | (w[i].z ^ flag) | (w[i].w ^ flag);
            }
            if (!__any_sync(0xffffffffu, bad & 1u)) break;
        }
        if (tid == 0) TS(16);
        float v[4];
        v[0] = (__uint_as_float(w[0].x) + __uint_as_float(w[1].x)) + (__uint_as_float(w[2].x) + __uint_as_float(w[3].x));
        v[1] = (__uint_as_float(w[0].y) + __uint_as_float(w[1].y)) + (__uint_as_float(w[2].y) + __uint_as_float(w[3].y));
        v[2] = (__uint_as_float(w[0].z) + __uint_as_float(w[1].z)) + (__uint_as_float(w[2].z) + __uint_as_float(w[3].z));
        v[3] = (__uint_as_float(w[0].w) + __uint_as_float(w[1].w)) + (__uint_as_float(w[2].w) + __uint_as_float(w[3].w));
#pragma unroll
        for (int j = 0; j < 4; j++) {
            v[j] += __shfl_xor_sync(0xffffffffu, v[j], 8);
            v[j] += __shfl_xor_sync(0xffffffffu, v[j], 16);
        }
        if (lane < 8) {
            const int rc = cta / 9, ntc = cta - 9 * rc;
            uint2 pk;
            pk.x = pack_bf16(x_fin[0] + bfr(bfr(v[0]) * gate[0]), x_fin[1] + bfr(bfr(v[1]) * gate[1]));
            pk.y = pack_bf16(x_fin[2] + bfr(bfr(v[2]) * gate[2]), x_fin[3] + bfr(bfr(v[3]) * gate[3]));
            *reinterpret_cast<uint2*>(out + (lane >> 1) * kD + kCols3 * rc + 8 * ntc + (lane & 1) * 4) = pk;
        }
        if (tid == 0) TS(17);
        if (cta == 0 && tid == 0) {
            asm volatile("st.relaxed.gpu.global.u32 [%0], %1;" ::"l"(&g_epoch), "r"(epoch + 1u) : "memory");
        }
    }
}

typedef CUresult (*PFN_encodeTiled)(CUtensorMap*, CUtensorMapDataType, cuuint32_t, void*, const cuuint64_t*,
                                    const cuuint64_t*, const cuuint32_t*, const cuuint32_t*, CUtensorMapInterleave,
                                    CUtensorMapSwizzle, CUtensorMapL2promotion, CUtensorMapFloatOOBfill);

void make_map(PFN_encodeTiled enc, CUtensorMap* map, const void* ptr, uint64_t cols, uint64_t rows, uint32_t box_c,
              uint32_t box_r, CUtensorMapSwizzle swz, CUtensorMapL2promotion promo) {
    cuuint64_t gdim[2] = {cols, rows};
    cuuint64_t gstr[1] = {cols * 2};
    cuuint32_t box[2] = {box_c, box_r};
    cuuint32_t estr[2] = {1, 1};
    enc(map, CU_TENSOR_MAP_DATA_TYPE_BFLOAT16, 2, const_cast<void*>(ptr), gdim, gstr, box, estr,
        CU_TENSOR_MAP_INTERLEAVE_NONE, swz, promo, CU_TENSOR_MAP_FLOAT_OOB_FILL_NONE);
}

}

extern "C" void kernel_launch(void* const* d_in, const int* in_sizes, int n_in, void* d_out, int out_size) {
    (void)in_sizes;
    (void)n_in;
    (void)out_size;
    static PFN_encodeTiled enc = nullptr;
    if (!enc) {
        void* fn = nullptr;
        cudaDriverEntryPointQueryResult st;
        cudaGetDriverEntryPoint("cuTensorMapEncodeTiled", &fn, cudaEnableDefault, &st);
        enc = (PFN_encodeTiled)fn;
        cudaFuncSetAttribute(fused_decode_kernel, cudaFuncAttributeMaxDynamicSharedMemorySize, SMEM_BYTES);
    }
    CUtensorMap kmap, vmap, womap, w2map, wqmap, w1map;
    make_map(enc, &wqmap, d_in[3], kNQ, kD, 32, 144, CU_TENSOR_MAP_SWIZZLE_64B, CU_TENSOR_MAP_L2_PROMOTION_L2_128B);
    make_map(enc, &w1map, d_in[6], kF, kD, 40, 144, CU_TENSOR_MAP_SWIZZLE_NONE, CU_TENSOR_MAP_L2_PROMOTION_L2_128B);
    make_map(enc, &kmap, d_in[1], kDh, (uint64_t)kB * kHkv * kSk, 64, kChunkKeys, CU_TENSOR_MAP_SWIZZLE_128B,
             CU_TENSOR_MAP_L2_PROMOTION_L2_256B);
    make_map(enc, &vmap, d_in[2], kDh, (uint64_t)kB * kHkv * kSk, 64, kChunkKeys, CU_TENSOR_MAP_SWIZZLE_128B,
             CU_TENSOR_MAP_L2_PROMOTION_L2_256B);
    make_map(enc, &womap, d_in[4], kD, kNQ, kCols3, 128, CU_TENSOR_MAP_SWIZZLE_NONE,
             CU_TENSOR_MAP_L2_PROMOTION_L2_128B);
    make_map(enc, &w2map, d_in[7], kD, kF, kCols3, 144, CU_TENSOR_MAP_SWIZZLE_NONE,
             CU_TENSOR_MAP_L2_PROMOTION_L2_128B);
    fused_decode_kernel<<<kCTAs, 288, SMEM_BYTES>>>(kmap, vmap, womap, w2map, wqmap, w1map,
                                                    (const __nv_bfloat16*)d_in[0], (__nv_bfloat16*)d_out);
}
```

```cpp
#include <cuda_runtime.h>
#include <cuda_bf16.h>
#include <cuda.h>
#include <stdint.h>

namespace {

constexpr int kB = 4, kD = 576, kHkv = 16, kSk = 4096, kDh = 128, kWin = 1024, kF = 4608;
constexpr int kNQ = 4096;
constexpr int kGroups = 16, kRanks = 8, kCTAs = 128;
constexpr int kRows1 = 72;
constexpr int kQCols = 256, kHCols = 288;
constexpr int kCols3 = 72;
constexpr int kChunkKeys = 64;
constexpr int kFinalCons = 72;

constexpr int kSlotBytes = 16384;
constexpr int OFF_KV = 0;
constexpr int STR_W3 = 144;
constexpr int BOX_WQ = 144 * 64;
constexpr int BOX_W1 = 144 * 80;
constexpr int OFF_A = 8 * kSlotBytes;
constexpr int SZ_A = 4 * BOX_WQ;
constexpr int OFF_B = OFF_A + SZ_A;
constexpr int SZ_B = 4 * BOX_W1;
constexpr int OFF_XN = OFF_B + SZ_B;
constexpr int OFF_Q = OFF_XN + 4 * 584 * 2;
constexpr int OFF_H = OFF_Q + 544;
constexpr int OFF_O = OFF_H + 4 * 296 * 2;
constexpr int OFF_P = OFF_O + 4 * 264 * 2;
constexpr int OFF_ML = OFF_P + 2 * 520 * 2;
constexpr int OFF_STG = OFF_ML + 128;
constexpr int OFF_BAR = OFF_STG + 1024;
constexpr int SMEM_USED = OFF_BAR + 288;
constexpr int SMEM_BYTES = SMEM_USED + 1024;

static_assert(OFF_A % 128 == 0 && OFF_B % 128 == 0, "align");
static_assert(OFF_BAR % 8 == 0 && OFF_STG % 16 == 0, "align");
static_assert(SMEM_BYTES <= 232448, "smem");

__device__ __align__(128) uint32_t g_qx[kGroups * kB * kQCols];
__device__ __align__(128) uint32_t g_hx[kGroups * kB * kHCols];
__device__ __align__(128) uint32_t g_opart[kGroups * kB * 2 * 2 * 136];
__device__ __align__(128) uint32_t g_fpart[kFinalCons * 2 * kGroups * 32];
__device__ uint32_t g_epoch;

constexpr int kSpinLimit = 1 << 22;
#define KWINDOW 3
constexpr int kWindow = KWINDOW;

#define ORDER 2
#define G_FIRST (ORDER == 1 || ORDER == 2 || ORDER == 4)
__constant__ int c_order[24] = {0, 1, 2, 3, 4, 5, 6, 7, 8, 9, 10, 11, 20, 21, 12, 13, 14, 15, 16, 17, 18, 19, 22, 23};

#define TS(k)
#define TS2(k)

__device__ __forceinline__ uint32_t smem_u32(const void* p) {
    return (uint32_t)__cvta_generic_to_shared(p);
}
__device__ __forceinline__ void mbar_init(uint32_t bar, uint32_t count) {
    asm volatile("mbarrier.init.shared::cta.b64 [%0], %1;" ::"r"(bar), "r"(count) : "memory");
}
__device__ __forceinline__ void mbar_expect_tx(uint32_t bar, uint32_t bytes) {
    asm volatile("mbarrier.arrive.expect_tx.shared::cta.b64 _, [%0], %1;" ::"r"(bar), "r"(bytes) : "memory");
}
__device__ __forceinline__ void mbar_arrive(uint32_t bar) {
    asm volatile("mbarrier.arrive.shared::cta.b64 _, [%0];" ::"r"(bar) : "memory");
}
__device__ __forceinline__ bool mbar_try_wait(uint32_t bar, uint32_t parity) {
    uint32_t ok;
    asm volatile(
        "{\n .reg .pred p;\n mbarrier.try_wait.parity.shared::cta.b64 p, [%1], %2;\n selp.u32 %0, 1, 0, p;\n}"
        : "=r"(ok)
        : "r"(bar), "r"(parity)
        : "memory");
    return ok != 0;
}
__device__ __forceinline__ void mbar_wait(uint32_t bar, uint32_t parity) {
    for (int i = 0; i < kSpinLimit; i++) {
        if (mbar_try_wait(bar, parity)) break;
    }
}
__device__ __forceinline__ void bulk_g2s(uint32_t dst, const void* src, uint32_t bytes, uint32_t bar) {
    asm volatile(
        "cp.async.bulk.shared::cluster.global.mbarrier::complete_tx::bytes [%0], [%1], %2, [%3];" ::"r"(dst),
        "l"(src), "r"(bytes), "r"(bar)
        : "memory");
}
__device__ __forceinline__ void tma_2d_ef(uint32_t dst, const CUtensorMap* map, int c0, int c1, uint32_t bar) {
    uint64_t pol;
    asm volatile("createpolicy.fractional.L2::evict_first.b64 %0, 1.0;" : "=l"(pol));
    asm volatile(
        "cp.async.bulk.tensor.2d.shared::cluster.global.mbarrier::complete_tx::bytes.L2::cache_hint [%0], [%1, {%3, %4}], [%2], %5;" ::"r"(dst),
        "l"(map), "r"(bar), "r"(c0), "r"(c1), "l"(pol)
        : "memory");
}
__device__ __forceinline__ void tma_2d(uint32_t dst, const CUtensorMap* map, int c0, int c1, uint32_t bar) {
    asm volatile(
        "cp.async.bulk.tensor.2d.shared::cluster.global.mbarrier::complete_tx::bytes [%0], [%1, {%3, %4}], [%2];" ::"r"(dst),
        "l"(map), "r"(bar), "r"(c0), "r"(c1)
        : "memory");
}
__device__ __forceinline__ void ldsm_x4(uint32_t addr, uint32_t& r0, uint32_t& r1, uint32_t& r2, uint32_t& r3) {
    asm volatile("ldmatrix.sync.aligned.m8n8.x4.shared.b16 {%0,%1,%2,%3}, [%4];"
                 : "=r"(r0), "=r"(r1), "=r"(r2), "=r"(r3)
                 : "r"(addr)
                 : "memory");
}
__device__ __forceinline__ void ldsm_x4_t(uint32_t addr, uint32_t& r0, uint32_t& r1, uint32_t& r2, uint32_t& r3) {
    asm volatile("ldmatrix.sync.aligned.m8n8.x4.trans.shared.b16 {%0,%1,%2,%3}, [%4];"
                 : "=r"(r0), "=r"(r1), "=r"(r2), "=r"(r3)
                 : "r"(addr)
                 : "memory");
}
__device__ __forceinline__ void ldsm_x2_t(uint32_t addr, uint32_t& r0, uint32_t& r1) {
    asm volatile("ldmatrix.sync.aligned.m8n8.x2.trans.shared.b16 {%0,%1}, [%2];"
                 : "=r"(r0), "=r"(r1)
                 : "r"(addr)
                 : "memory");
}
__device__ __forceinline__ void mma16816(float (&c)[4], uint32_t a0, uint32_t a1, uint32_t a2, uint32_t a3,
                                         uint32_t b0, uint32_t b1) {
    asm volatile(
        "mma.sync.aligned.m16n8k16.row.col.f32.bf16.bf16.f32 {%0,%1,%2,%3}, {%4,%5,%6,%7}, {%8,%9}, {%0,%1,%2,%3};"
        : "+f"(c[0]), "+f"(c[1]), "+f"(c[2]), "+f"(c[3])
        : "r"(a0), "r"(a1), "r"(a2), "r"(a3), "r"(b0), "r"(b1));
}
__device__ __forceinline__ void mma1688(float (&c)[4], uint32_t a0, uint32_t a1, uint32_t b0) {
    asm volatile("mma.sync.aligned.m16n8k8.row.col.f32.bf16.bf16.f32 {%0,%1,%2,%3}, {%4,%5}, {%6}, {%0,%1,%2,%3};"
                 : "+f"(c[0]), "+f"(c[1]), "+f"(c[2]), "+f"(c[3])
                 : "r"(a0), "r"(a1), "r"(b0));
}
__device__ __forceinline__ void bar_cons() { asm volatile("bar.sync 1, 256;" ::: "memory"); }

__device__ __forceinline__ float bfr(float x) { return __bfloat162float(__float2bfloat16_rn(x)); }
__device__ __forceinline__ uint32_t pack_bf16(float lo, float hi) {
    __nv_bfloat162 v = __floats2bfloat162_rn(lo, hi);
    return *reinterpret_cast<uint32_t*>(&v);
}
__device__ __forceinline__ uint32_t tagw(float v, uint32_t flag) { return (__float_as_uint(v) & ~1u) | flag; }
__device__ __forceinline__ void st_word(uint32_t* p, uint32_t v) {
    asm volatile("st.relaxed.gpu.global.u32 [%0], %1;" ::"l"(p), "r"(v) : "memory");
}
__device__ __forceinline__ void st_word2(uint32_t* p, uint32_t v0, uint32_t v1) {
    asm volatile("st.relaxed.gpu.global.v2.u32 [%0], {%1,%2};" ::"l"(p), "r"(v0), "r"(v1) : "memory");
}
__device__ __forceinline__ void st_word4(uint32_t* p, uint32_t v) {
    asm volatile("st.relaxed.gpu.global.v4.u32 [%0], {%1,%1,%1,%1};" ::"l"(p), "r"(v) : "memory");
}
__device__ __forceinline__ void st_word4v(uint32_t* p, uint32_t a, uint32_t b, uint32_t c, uint32_t d) {
    asm volatile("st.relaxed.gpu.global.v4.u32 [%0], {%1,%2,%3,%4};" ::"l"(p), "r"(a), "r"(b), "r"(c), "r"(d) : "memory");
}
__device__ __forceinline__ uint32_t ld_word(const uint32_t* p) {
    uint32_t v;
    asm volatile("ld.relaxed.gpu.global.u32 %0, [%1];" : "=r"(v) : "l"(p) : "memory");
    return v;
}
__device__ __forceinline__ uint2 ld_word2(const uint32_t* p) {
    uint2 v;
    asm volatile("ld.relaxed.gpu.global.v2.u32 {%0,%1}, [%2];" : "=r"(v.x), "=r"(v.y) : "l"(p) : "memory");
    return v;
}
__device__ __forceinline__ uint4 ld_word4(const uint32_t* p) {
    uint4 v;
    asm volatile("ld.relaxed.gpu.global.v4.u32 {%0,%1,%2,%3}, [%4];"
                 : "=r"(v.x), "=r"(v.y), "=r"(v.z), "=r"(v.w)
                 : "l"(p)
                 : "memory");
    return v;
}
__device__ __forceinline__ float silu_f(float x) { return x / (1.0f + __expf(-x)); }

template <int KSTEPS, int ASTRIDE>
__device__ __forceinline__ void gemv3_tile(uint32_t wbuf, const __nv_bfloat16* act, int nt, int lane, float (&c)[4]) {
    const int gid = lane >> 2, tig = lane & 3, lm_i = lane & 7, lm_j = lane >> 3;
    const uint32_t wb = wbuf + (8 * lm_j + lm_i) * STR_W3 + nt * 16;
    const __nv_bfloat16* ap = act + (gid & 3) * ASTRIDE + 2 * tig;
    float acc[4][4];
#pragma unroll
    for (int i = 0; i < 4; i++) acc[i][0] = acc[i][1] = acc[i][2] = acc[i][3] = 0.f;
#pragma unroll
    for (int kk = 0; kk < KSTEPS / 2; kk++) {
        uint32_t b0, b1, b2, b3;
        ldsm_x4_t(wb + kk * 32 * STR_W3, b0, b1, b2, b3);
        uint32_t a0 = *reinterpret_cast<const uint32_t*>(ap + 32 * kk);
        uint32_t a2 = *reinterpret_cast<const uint32_t*>(ap + 32 * kk + 8);
        uint32_t a4 = *reinterpret_cast<const uint32_t*>(ap + 32 * kk + 16);
        uint32_t a6 = *reinterpret_cast<const uint32_t*>(ap + 32 * kk + 24);
        if (gid >= 4) a0 = a2 = a4 = a6 = 0u;
        mma16816(acc[(2 * kk) & 3], a0, 0u, a2, 0u, b0, b1);
        mma16816(acc[(2 * kk + 1) & 3], a4, 0u, a6, 0u, b2, b3);
    }
    c[0] = (acc[0][0] + acc[1][0]) + (acc[2][0] + acc[3][0]);
    c[1] = (acc[0][1] + acc[1][1]) + (acc[2][1] + acc[3][1]);
    c[2] = c[3] = 0.f;
}

__global__ void __launch_bounds__(288, 1)
fused_decode_kernel(const __grid_constant__ CUtensorMap kmap, const __grid_constant__ CUtensorMap vmap,
                    const __grid_constant__ CUtensorMap womap, const __grid_constant__ CUtensorMap w2map,
                    const __grid_constant__ CUtensorMap wqmap, const __grid_constant__ CUtensorMap w1map,
                    const __nv_bfloat16* __restrict__ x, __nv_bfloat16* __restrict__ out) {
    extern __shared__ uint8_t smem_raw[];
    const uint32_t raw_u32 = smem_u32(smem_raw);
    const uint32_t sbase = (raw_u32 + 1023u) & ~1023u;
    uint8_t* sgen = smem_raw + (sbase - raw_u32);

    const int tid = threadIdx.x, warp = tid >> 5, lane = tid & 31;
    const int cta = blockIdx.x;
    const int g = cta >> 3, r = cta & 7;
    const int b = r >> 1, half = r & 1;

    const uint32_t bar_full = sbase + OFF_BAR;
    const uint32_t bar_empty = sbase + OFF_BAR + 24 * 8;
    const uint32_t bar_s1 = sbase + OFF_BAR + 32 * 8;

    const int kv_row0 = (b * kHkv + g) * kSk + (kSk - kWin) + half * 512;
    const int hst = (36 * r) >> 3;
    const int hcnt = ((36 * (r + 1)) >> 3) - hst;

    if (warp == 8) {
        if (lane == 0) {
            TS(0);
            for (int i = 0; i < 32; i++) mbar_init(bar_full + 8 * i, 1);
            mbar_init(bar_s1, 8);
            asm volatile("fence.mbarrier_init.release.cluster;" ::: "memory");
            asm volatile("fence.proxy.async.shared::cta;" ::: "memory");
        }
        __syncwarp();
        asm volatile("bar.arrive 2, 288;" ::: "memory");
#pragma unroll 1
        for (int n = 0; n < 24; n++) {
            const int u = c_order[n];
            if (n >= kWindow) mbar_wait(bar_full + 8 * c_order[n - kWindow], 0);
            const uint32_t bar = bar_full + 8 * u;
            if (u < 2) {
                if (lane == 0) {
                    mbar_expect_tx(bar, 2 * BOX_WQ);
                    tma_2d(sbase + OFF_A + (2 * u) * BOX_WQ, &wqmap, kQCols * g + 32 * r, 144 * (2 * u), bar);
                    tma_2d(sbase + OFF_A + (2 * u + 1) * BOX_WQ, &wqmap, kQCols * g + 32 * r, 144 * (2 * u + 1), bar);
                }
            } else if (u < 4) {
                if (lane == 0) {
                    mbar_expect_tx(bar, 2 * BOX_W1);
                    tma_2d(sbase + OFF_B + (2 * u - 4) * BOX_W1, &w1map, kHCols * g + 8 * hst, 144 * (2 * u - 4), bar);
                    tma_2d(sbase + OFF_B + (2 * u - 3) * BOX_W1, &w1map, kHCols * g + 8 * hst, 144 * (2 * u - 3), bar);
                }
            } else if (u < 20) {
                const int c = (u - 4) & 7;
                if (u >= 12) mbar_wait(bar_empty + 8 * c, 0);
                if (lane == 0) {
                    const CUtensorMap* mp = u >= 12 ? &vmap : &kmap;
                    mbar_expect_tx(bar, kSlotBytes);
                    tma_2d_ef(sbase + OFF_KV + c * kSlotBytes, mp, 0, kv_row0 + kChunkKeys * c, bar);
                    tma_2d_ef(sbase + OFF_KV + c * kSlotBytes + 8192, mp, 64, kv_row0 + kChunkKeys * c, bar);
                }
            } else if (u < 22) {
                mbar_wait(bar_s1, 0);
                if (lane == 0) {
                    mbar_expect_tx(bar, 144 * STR_W3);
                    tma_2d(sbase + OFF_B + (u - 20) * 144 * STR_W3, &w2map, kCols3 * r, kHCols * g + 144 * (u - 20), bar);
                }
            } else {
                mbar_wait(bar_s1, 0);
                if (lane == 0) {
                    mbar_expect_tx(bar, 128 * STR_W3);
                    tma_2d(sbase + OFF_A + (u - 22) * 128 * STR_W3, &womap, kCols3 * r, kQCols * g + 128 * (u - 22), bar);
                }
            }
            if (lane == 0) TS2(n);
            __syncwarp();
        }
        asm volatile("bar.sync 3, 288;" ::: "memory");
        mbar_wait(bar_full + 8 * 22, 0);
        mbar_wait(bar_full + 8 * 23, 0);
        const uint32_t flag_p = *reinterpret_cast<volatile uint32_t*>(sgen + OFF_BAR + 280);
        {
            float c[4];
            gemv3_tile<16, 264>(sbase + OFF_A, reinterpret_cast<const __nv_bfloat16*>(sgen + OFF_O), 8, lane, c);
            if ((lane >> 2) < 4)
                st_word2(g_fpart + (size_t)(((r * 9 + 8) * 2 + 0) * kGroups + g) * 32 + (lane >> 2) * 8 + 2 * (lane & 3),
                         tagw(c[0], flag_p), tagw(c[1], flag_p));
        }
        return;
    }

    uint32_t epoch;
    asm volatile("ld.relaxed.gpu.global.u32 %0, [%1];" : "=r"(epoch) : "l"(&g_epoch) : "memory");
    uint32_t xw[9];
    if (warp < 4) {
        const uint32_t* xr = reinterpret_cast<const uint32_t*>(x + warp * kD);
#pragma unroll
        for (int i = 0; i < 9; i++) xw[i] = __ldg(xr + lane + 32 * i);
    }
    float x_fin[4] = {0.f, 0.f, 0.f, 0.f};
    if (cta < kFinalCons && tid < 8) {
        const int rc = cta / 9, ntc = cta - 9 * rc;
        const uint2 xv = __ldg(reinterpret_cast<const uint2*>(x + (tid >> 1) * kD + kCols3 * rc + 8 * ntc + (tid & 1) * 4));
        x_fin[0] = __uint_as_float(xv.x << 16);
        x_fin[1] = __uint_as_float(xv.x & 0xffff0000u);
        x_fin[2] = __uint_as_float(xv.y << 16);
        x_fin[3] = __uint_as_float(xv.y & 0xffff0000u);
    }
    const uint32_t flag = (epoch + 1u) & 1u;

    __nv_bfloat16* xn_s = reinterpret_cast<__nv_bfloat16*>(sgen + OFF_XN);
    __nv_bfloat16* q_s = reinterpret_cast<__nv_bfloat16*>(sgen + OFF_Q);
    __nv_bfloat16* h_s = reinterpret_cast<__nv_bfloat16*>(sgen + OFF_H);
    __nv_bfloat16* o_s = reinterpret_cast<__nv_bfloat16*>(sgen + OFF_O);
    __nv_bfloat16* p_s = reinterpret_cast<__nv_bfloat16*>(sgen + OFF_P);
    float* ml_s = reinterpret_cast<float*>(sgen + OFF_ML);

    if (tid == 0) *reinterpret_cast<volatile uint32_t*>(sgen + OFF_BAR + 280) = flag;
    {
        const uint32_t inv = flag ^ 1u;
        if (tid < 32) {
            st_word4(g_qx + (size_t)(g * kB + (tid >> 3)) * kQCols + 32 * r + 4 * (tid & 7), inv);
        } else if (tid < 32 + 40) {
            {
            const int i = tid - 32, bb = i / 10, c4 = i - bb * 10;
            if (c4 < 2 * hcnt) st_word4(g_hx + (size_t)(g * kB + bb) * kHCols + 8 * hst + 4 * c4, inv);
            }
        } else if (tid >= 96 && tid < 96 + 68) {
            st_word4(g_opart + (size_t)((g * kB + b) * 2 + half) * 272 + 4 * (tid - 96), inv);
        } else if (tid >= 184) {
            const int i = tid - 184;
            const int nt = i >> 3, c4 = i & 7;
            st_word4(g_fpart + (size_t)(((r * 9 + nt) * 2 + 0) * kGroups + g) * 32 + 4 * c4, inv);
        }
    }

    if (warp < 4) {
        float v[18];
        float sum = 0.f;
#pragma unroll
        for (int i = 0; i < 9; i++) {
            v[2 * i] = __uint_as_float(xw[i] << 16);
            v[2 * i + 1] = __uint_as_float(xw[i] & 0xffff0000u);
            sum += v[2 * i] + v[2 * i + 1];
        }
#pragma unroll
        for (int o = 16; o > 0; o >>= 1) sum += __shfl_xor_sync(0xffffffffu, sum, o);
        const float mean = sum * (1.0f / kD);
        float sq = 0.f;
#pragma unroll
        for (int i = 0; i < 18; i++) {
            float d = v[i] - mean;
            sq += d * d;
        }
#pragma unroll
        for (int o = 16; o > 0; o >>= 1) sq += __shfl_xor_sync(0xffffffffu, sq, o);
        const float m_bf = bfr(mean);
        const float v_bf = bfr(sq * (1.0f / kD));
        const float den = bfr(sqrtf(bfr(v_bf + 1e-5f)));
#pragma unroll
        for (int i = 0; i < 9; i++) {
            const float a0 = bfr(v[2 * i] - m_bf) / den;
            const float a1 = bfr(v[2 * i + 1] - m_bf) / den;
            *reinterpret_cast<uint32_t*>(xn_s + warp * 584 + 2 * (lane + 32 * i)) = pack_bf16(a0, a1);
        }
    }
    asm volatile("bar.sync 2, 288;" ::: "memory");
    if (tid == 0) TS(1);

    const int gid = lane >> 2, tig = lane & 3;
    const int lm_i = lane & 7, lm_j = lane >> 3;

    {
        const __nv_bfloat16* ap = xn_s + (gid & 3) * 584 + 2 * tig;
#pragma unroll 1
        for (int job = warp; job < 9; job += 8) {
            const bool isq = job < 4;
            const int nt = isq ? job : job - 4;
            if (!isq && nt >= hcnt) break;
            float acc[4][4];
#pragma unroll
            for (int i = 0; i < 4; i++) acc[i][0] = acc[i][1] = acc[i][2] = acc[i][3] = 0.f;
#pragma unroll 1
            for (int bx = 0; bx < 4; bx++) {
                if ((bx & 1) == 0) mbar_wait(bar_full + 8 * ((isq ? 0 : 2) + (bx >> 1)), 0);
#pragma unroll
                for (int kk = 0; kk < 5; kk++) {
                    const int row = 32 * kk + 8 * lm_j + lm_i;
                    uint32_t addr;
                    if (isq)
                        addr = sbase + OFF_A + bx * BOX_WQ + row * 64 + ((nt ^ ((row >> 1) & 3)) << 4);
                    else
                        addr = sbase + OFF_B + bx * BOX_W1 + row * 80 + nt * 16;
                    const int k0 = 144 * bx + 32 * kk;
                    uint32_t a0 = *reinterpret_cast<const uint32_t*>(ap + k0);
                    uint32_t a2 = *reinterpret_cast<const uint32_t*>(ap + k0 + 8);
                    if (gid >= 4) a0 = a2 = 0u;
                    if (kk < 4) {
                        uint32_t b0, b1, b2, b3;
                        ldsm_x4_t(addr, b0, b1, b2, b3);
                        uint32_t a4 = *reinterpret_cast<const uint32_t*>(ap + k0 + 16);
                        uint32_t a6 = *reinterpret_cast<const uint32_t*>(ap + k0 + 24);
                        if (gid >= 4) a4 = a6 = 0u;
                        mma16816(acc[(2 * kk) & 3], a0, 0u, a2, 0u, b0, b1);
                        mma16816(acc[(2 * kk + 1) & 3], a4, 0u, a6, 0u, b2, b3);
                    } else {
                        uint32_t b0, b1;
                        ldsm_x2_t(addr, b0, b1);
                        mma16816(acc[0], a0, 0u, a2, 0u, b0, b1);
                    }
                }
            }
            float c0 = (acc[0][0] + acc[1][0]) + (acc[2][0] + acc[3][0]);
            float c1 = (acc[0][1] + acc[1][1]) + (acc[2][1] + acc[3][1]);
            if (gid < 4) {
                if (isq) {
                    const uint32_t pk = pack_bf16(c0, c1);
                    st_word2(g_qx + (size_t)(g * kB + gid) * kQCols + 32 * r + 8 * nt + 2 * tig, (pk << 16) | flag,
                             (pk & 0xffff0000u) | flag);
                } else {
                    const uint32_t pk = pack_bf16(silu_f(bfr(c0)), silu_f(bfr(c1)));
                    st_word2(g_hx + (size_t)(g * kB + gid) * kHCols + 8 * (hst + nt) + 2 * tig, (pk << 16) | flag,
                             (pk & 0xffff0000u) | flag);
                }
            }
        }
        if (tid == 0) TS(3);
    }
    __syncwarp();
    if (lane == 0) mbar_arrive(bar_s1);

    if (tid < 64) {
        const uint32_t* src = g_qx + (size_t)(g * kB + b) * kQCols + 4 * tid;
        uint4 w;
        for (int it = 0; it < kSpinLimit; it++) {
            w = ld_word4(src);
            const uint32_t bad = (w.x ^ flag) | (w.y ^ flag) | (w.z ^ flag) | (w.w ^ flag);
            if (!(bad & 1u)) break;
        }
        uint2 pk;
        pk.x = (w.x >> 16) | (w.y & 0xffff0000u);
        pk.y = (w.z >> 16) | (w.w & 0xffff0000u);
        *reinterpret_cast<uint2*>(q_s + (tid >> 5) * 136 + 4 * (tid & 31)) = pk;
    }
    bar_cons();
    if (tid == 0) TS(4);

    float sc[8][2];
    {
        const uint32_t slot = sbase + OFF_KV + warp * kSlotBytes;
        uint32_t qa[16];
#pragma unroll
        for (int j = 0; j < 8; j++) {
            qa[2 * j] = gid < 2 ? *reinterpret_cast<const uint32_t*>(q_s + gid * 136 + 16 * j + 2 * tig) : 0u;
            qa[2 * j + 1] = gid < 2 ? *reinterpret_cast<const uint32_t*>(q_s + gid * 136 + 16 * j + 8 + 2 * tig) : 0u;
        }
        mbar_wait(bar_full + 8 * (4 + warp), 0);
        if (tid == 0) TS(5);
        if (tid == 224) TS(7);
        float mx = -INFINITY;
        const float scale = 0.08838834764831845f;
#pragma unroll
        for (int nt = 0; nt < 8; nt++) {
            float acc[4] = {0.f, 0.f, 0.f, 0.f};
#pragma unroll
            for (int kk = 0; kk < 4; kk++) {
                const int cg = 4 * kk + lm_j;
                const uint32_t addr =
                    slot + (cg >> 3) * 8192 + (8 * nt + lm_i) * 128 + (((cg & 7) ^ lm_i) << 4);
                uint32_t b0, b1, b2, b3;
                ldsm_x4(addr, b0, b1, b2, b3);
                mma16816(acc, qa[4 * kk], 0u, qa[4 * kk + 1], 0u, b0, b1);
                mma16816(acc, qa[4 * kk + 2], 0u, qa[4 * kk + 3], 0u, b2, b3);
            }
            sc[nt][0] = bfr(bfr(acc[0]) * scale);
            sc[nt][1] = bfr(bfr(acc[1]) * scale);
            mx = fmaxf(mx, fmaxf(sc[nt][0], sc[nt][1]));
        }
        __syncwarp();
        if (lane == 0) mbar_arrive(bar_empty + 8 * warp);
        mx = fmaxf(mx, __shfl_xor_sync(0xffffffffu, mx, 1));
        mx = fmaxf(mx, __shfl_xor_sync(0xffffffffu, mx, 2));
        if (lane == 0 || lane == 4) ml_s[(lane >> 2) * 8 + warp] = mx;
    }

    {
        for (int idx = tid; idx < kB * kHCols / 4; idx += 256) {
            const uint32_t* src = g_hx + (size_t)g * kB * kHCols + 4 * idx;
            uint4 w;
            for (int it = 0; it < kSpinLimit; it++) {
                w = ld_word4(src);
                const uint32_t bad = (w.x ^ flag) | (w.y ^ flag) | (w.z ^ flag) | (w.w ^ flag);
                if (!(bad & 1u)) break;
            }
            const int bb = idx / 72, c4 = idx - bb * 72;
            uint2 pk;
            pk.x = (w.x >> 16) | (w.y & 0xffff0000u);
            pk.y = (w.z >> 16) | (w.w & 0xffff0000u);
            *reinterpret_cast<uint2*>(h_s + bb * 296 + 4 * c4) = pk;
        }
        if (tid == 0) TS(10);
    }
    bar_cons();

    {
        const int hh = gid & 1;
        float M = ml_s[hh * 8];
#pragma unroll
        for (int w = 1; w < 8; w++) M = fmaxf(M, ml_s[hh * 8 + w]);
        const float l2e = 1.4426950408889634f;
        float lsum = 0.f;
#pragma unroll
        for (int nt = 0; nt < 8; nt++) {
            const float p0 = exp2f((sc[nt][0] - M) * l2e);
            const float p1 = exp2f((sc[nt][1] - M) * l2e);
            lsum += p0 + p1;
            if (gid < 2) *reinterpret_cast<uint32_t*>(p_s + gid * 520 + 64 * warp + 8 * nt + 2 * tig) = pack_bf16(p0, p1);
        }
        lsum += __shfl_xor_sync(0xffffffffu, lsum, 1);
        lsum += __shfl_xor_sync(0xffffffffu, lsum, 2);
        if (lane == 0 || lane == 4) ml_s[16 + (lane >> 2) * 8 + warp] = lsum;
    }
    bar_cons();

    {
        float oc[2][4] = {{0.f, 0.f, 0.f, 0.f}, {0.f, 0.f, 0.f, 0.f}};
        const int cg = 2 * warp + (lm_j & 1);
        const uint32_t vbase = sbase + OFF_KV + (cg >> 3) * 8192 + ((lm_j >> 1) * 8 + lm_i) * 128 + (((cg & 7) ^ lm_i) << 4);
        const __nv_bfloat16* pp = p_s + (gid & 1) * 520 + 2 * tig;
#pragma unroll 1
        for (int c = 0; c < 8; c++) {
            uint32_t pb[8];
#pragma unroll
            for (int j = 0; j < 8; j++) {
                pb[j] = *reinterpret_cast<const uint32_t*>(pp + 64 * c + 8 * j);
                if (gid >= 2) pb[j] = 0u;
            }
            if (c == 3) {
                mbar_wait(bar_full + 8 * 20, 0);
                mbar_wait(bar_full + 8 * 21, 0);
                for (int nt = 7 - warp; nt < 9; nt += 8) {
                    float cc[4];
                    gemv3_tile<18, 296>(sbase + OFF_B, h_s, nt, lane, cc);
                    if (gid < 4)
                        st_word2(g_fpart + (size_t)(((r * 9 + nt) * 2 + 1) * kGroups + g) * 32 + gid * 8 + 2 * tig,
                                 tagw(cc[0], flag), tagw(cc[1], flag));
                }
            }
            mbar_wait(bar_full + 8 * (12 + c), 0);
            if (tid == 0 && c == 0) TS(6);
            if (tid == 0 && c == 7) TS(8);
#pragma unroll
            for (int ks = 0; ks < 4; ks++) {
                uint32_t a0, a1, a2, a3;
                ldsm_x4_t(vbase + c * kSlotBytes + ks * 16 * 128, a0, a1, a2, a3);
                mma16816(oc[ks & 1], a0, a1, a2, a3, pb[2 * ks], pb[2 * ks + 1]);
            }
        }
        uint32_t* od = g_opart + (size_t)((g * kB + b) * 2 + half) * 272;
        float* stg = reinterpret_cast<float*>(sgen + OFF_STG) + warp * 32;
        if (tig == 0) {
            stg[gid] = oc[0][0] + oc[1][0];
            stg[16 + gid] = oc[0][1] + oc[1][1];
            stg[gid + 8] = oc[0][2] + oc[1][2];
            stg[16 + gid + 8] = oc[0][3] + oc[1][3];
        }
        __syncwarp();
        if (lane < 8) {
            const float4 v = *reinterpret_cast<const float4*>(stg + 4 * lane);
            st_word4v(od + (lane >> 2) * 128 + 16 * warp + 4 * (lane & 3), tagw(v.x, flag), tagw(v.y, flag),
                      tagw(v.z, flag), tagw(v.w, flag));
        } else if (warp == 0 && lane == 8) {
            float M0 = ml_s[0], L0 = ml_s[16], M1 = ml_s[8], L1 = ml_s[24];
#pragma unroll
            for (int w = 1; w < 8; w++) {
                M0 = fmaxf(M0, ml_s[w]);
                L0 += ml_s[16 + w];
                M1 = fmaxf(M1, ml_s[8 + w]);
                L1 += ml_s[24 + w];
            }
            st_word4v(od + 256, tagw(M0, flag), tagw(L0, flag), tagw(M1, flag), tagw(L1, flag));
        }
    }
    if (tid == 0) TS(13);

    uint4 wg[4];
    const uint32_t* gsrc = g_fpart + (size_t)cta * 1024 + 512 + (lane >> 3) * 4 * 32 + (lane & 7) * 4;
    if (cta < kFinalCons && warp == 0) {
#pragma unroll
        for (int i = 0; i < 4; i++) wg[i] = ld_word4(gsrc + i * 32);
    }

    {
        const int bb = tid >> 6, head = (tid >> 5) & 1, d4 = tid & 31;
        const uint32_t* src = g_opart + (size_t)((g * kB + bb) * 2) * 272;
        uint4 wa, wb2, sa, sb;
        if (tid == 0) TS(18);
        for (int it = 0; it < kSpinLimit; it++) {
            wa = ld_word4(src + head * 128 + 4 * d4);
            wb2 = ld_word4(src + 272 + head * 128 + 4 * d4);
            sa = ld_word4(src + 256);
            sb = ld_word4(src + 272 + 256);
            const uint32_t bad = (wa.x ^ flag) | (wa.y ^ flag) | (wa.z ^ flag) | (wa.w ^ flag) | (wb2.x ^ flag) |
                                 (wb2.y ^ flag) | (wb2.z ^ flag) | (wb2.w ^ flag) | (sa.x ^ flag) | (sa.y ^ flag) |
                                 (sa.z ^ flag) | (sa.w ^ flag) | (sb.x ^ flag) | (sb.y ^ flag) | (sb.z ^ flag) |
                                 (sb.w ^ flag);
            if (!(bad & 1u)) break;
        }
        if (tid == 0) TS(19);
        if (tid == 255) TS(20);
        const float m0 = __uint_as_float(head ? sa.z : sa.x), l0 = __uint_as_float(head ? sa.w : sa.y);
        const float m1 = __uint_as_float(head ? sb.z : sb.x), l1 = __uint_as_float(head ? sb.w : sb.y);
        const float MM = fmaxf(m0, m1);
        const float e0 = exp2f((m0 - MM) * 1.4426950408889634f), e1 = exp2f((m1 - MM) * 1.4426950408889634f);
        const float inv = 1.0f / (e0 * l0 + e1 * l1);
        const float f0 = e0 * inv, f1 = e1 * inv;
        uint2 pk;
        pk.x = pack_bf16(f0 * __uint_as_float(wa.x) + f1 * __uint_as_float(wb2.x),
                         f0 * __uint_as_float(wa.y) + f1 * __uint_as_float(wb2.y));
        pk.y = pack_bf16(f0 * __uint_as_float(wa.z) + f1 * __uint_as_float(wb2.z),
                         f0 * __uint_as_float(wa.w) + f1 * __uint_as_float(wb2.w));
        *reinterpret_cast<uint2*>(o_s + bb * 264 + head * 128 + 4 * d4) = pk;
    }
    asm volatile("bar.sync 3, 288;" ::: "memory");
    if (tid == 0) TS(9);
    mbar_wait(bar_full + 8 * 22, 0);
    mbar_wait(bar_full + 8 * 23, 0);
    if (tid == 0) TS(14);

    {
        float c[4];
        gemv3_tile<16, 264>(sbase + OFF_A, o_s, warp, lane, c);
        if (gid < 4)
            st_word2(g_fpart + (size_t)(((r * 9 + warp) * 2 + 0) * kGroups + g) * 32 + gid * 8 + 2 * tig,
                     tagw(c[0], flag), tagw(c[1], flag));
    }
    if (tid == 0) TS(15);

    if (cta < kFinalCons && warp == 0) {
        const uint32_t* src = g_fpart + (size_t)cta * 1024 + (lane >> 3) * 4 * 32 + (lane & 7) * 4;
        uint4 w[4];
#pragma unroll
        for (int i = 0; i < 4; i++) w[i] = ld_word4(src + i * 32);
        float gate[4];
        for (int it = 0; it < kSpinLimit; it++) {
            uint32_t bad = 0;
#pragma unroll
            for (int i = 0; i < 4; i++)
                bad |= (wg[i].x ^ flag) | (wg[i].y ^ flag) | (wg[i].z ^ flag) | (wg[i].w ^ flag);
            if (!__any_sync(0xffffffffu, bad & 1u)) break;
#pragma unroll
            for (int i = 0; i < 4; i++) wg[i] = ld_word4(gsrc + i * 32);
        }
        gate[0] = (__uint_as_float(wg[0].x) + __uint_as_float(wg[1].x)) + (__uint_as_float(wg[2].x) + __uint_as_float(wg[3].x));
        gate[1] = (__uint_as_float(wg[0].y) + __uint_as_float(wg[1].y)) + (__uint_as_float(wg[2].y) + __uint_as_float(wg[3].y));
        gate[2] = (__uint_as_float(wg[0].z) + __uint_as_float(wg[1].z)) + (__uint_as_float(wg[2].z) + __uint_as_float(wg[3].z));
        gate[3] = (__uint_as_float(wg[0].w) + __uint_as_float(wg[1].w)) + (__uint_as_float(wg[2].w) + __uint_as_float(wg[3].w));
#pragma unroll
        for (int j = 0; j < 4; j++) {
            gate[j] += __shfl_xor_sync(0xffffffffu, gate[j], 8);
            gate[j] += __shfl_xor_sync(0xffffffffu, gate[j], 16);
            gate[j] = bfr(silu_f(bfr(gate[j])));
        }
        for (int it = 0; it < kSpinLimit; it++) {
            uint32_t bad0 = 0;
#pragma unroll
            for (int i = 0; i < 4; i++)
                bad0 |= (w[i].x ^ flag) | (w[i].y ^ flag) | (w[i].z ^ flag) | (w[i].w ^ flag);
            if (!__any_sync(0xffffffffu, bad0 & 1u)) break;
#pragma unroll
            for (int i = 0; i < 4; i++) w[i] = ld_word4(src + i * 32);
        }
        if (tid == 0) TS(16);
        float v[4];
        v[0] = (__uint_as_float(w[0].x) + __uint_as_float(w[1].x)) + (__uint_as_float(w[2].x) + __uint_as_float(w[3].x));
        v[1] = (__uint_as_float(w[0].y) + __uint_as_float(w[1].y)) + (__uint_as_float(w[2].y) + __uint_as_float(w[3].y));
        v[2] = (__uint_as_float(w[0].z) + __uint_as_float(w[1].z)) + (__uint_as_float(w[2].z) + __uint_as_float(w[3].z));
        v[3] = (__uint_as_float(w[0].w) + __uint_as_float(w[1].w)) + (__uint_as_float(w[2].w) + __uint_as_float(w[3].w));
#pragma unroll
        for (int j = 0; j < 4; j++) {
            v[j] += __shfl_xor_sync(0xffffffffu, v[j], 8);
            v[j] += __shfl_xor_sync(0xffffffffu, v[j], 16);
        }
        if (lane < 8) {
            const int rc = cta / 9, ntc = cta - 9 * rc;
            uint2 pk;
            pk.x = pack_bf16(x_fin[0] + bfr(bfr(v[0]) * gate[0]), x_fin[1] + bfr(bfr(v[1]) * gate[1]));
            pk.y = pack_bf16(x_fin[2] + bfr(bfr(v[2]) * gate[2]), x_fin[3] + bfr(bfr(v[3]) * gate[3]));
            *reinterpret_cast<uint2*>(out + (lane >> 1) * kD + kCols3 * rc + 8 * ntc + (lane & 1) * 4) = pk;
        }
        if (tid == 0) TS(17);
        if (cta == 0 && tid == 0) {
            asm volatile("st.relaxed.gpu.global.u32 [%0], %1;" ::"l"(&g_epoch), "r"(epoch + 1u) : "memory");
        }
    }
}

typedef CUresult (*PFN_encodeTiled)(CUtensorMap*, CUtensorMapDataType, cuuint32_t, void*, const cuuint64_t*,
                                    const cuuint64_t*, const cuuint32_t*, const cuuint32_t*, CUtensorMapInterleave,
                                    CUtensorMapSwizzle, CUtensorMapL2promotion, CUtensorMapFloatOOBfill);

void make_map(PFN_encodeTiled enc, CUtensorMap* map, const void* ptr, uint64_t cols, uint64_t rows, uint32_t box_c,
              uint32_t box_r, CUtensorMapSwizzle swz, CUtensorMapL2promotion promo) {
    cuuint64_t gdim[2] = {cols, rows};
    cuuint64_t gstr[1] = {cols * 2};
    cuuint32_t box[2] = {box_c, box_r};
    cuuint32_t estr[2] = {1, 1};
    enc(map, CU_TENSOR_MAP_DATA_TYPE_BFLOAT16, 2, const_cast<void*>(ptr), gdim, gstr, box, estr,
        CU_TENSOR_MAP_INTERLEAVE_NONE, swz, promo, CU_TENSOR_MAP_FLOAT_OOB_FILL_NONE);
}

}

extern "C" void kernel_launch(void* const* d_in, const int* in_sizes, int n_in, void* d_out, int out_size) {
    (void)in_sizes;
    (void)n_in;
    (void)out_size;
    static PFN_encodeTiled enc = nullptr;
    if (!enc) {
        void* fn = nullptr;
        cudaDriverEntryPointQueryResult st;
        cudaGetDriverEntryPoint("cuTensorMapEncodeTiled", &fn, cudaEnableDefault, &st);
        enc = (PFN_encodeTiled)fn;
        cudaFuncSetAttribute(fused_decode_kernel, cudaFuncAttributeMaxDynamicSharedMemorySize, SMEM_BYTES);
    }
    CUtensorMap kmap, vmap, womap, w2map, wqmap, w1map;
    make_map(enc, &wqmap, d_in[3], kNQ, kD, 32, 144, CU_TENSOR_MAP_SWIZZLE_64B, CU_TENSOR_MAP_L2_PROMOTION_L2_128B);
    make_map(enc, &w1map, d_in[6], kF, kD, 40, 144, CU_TENSOR_MAP_SWIZZLE_NONE, CU_TENSOR_MAP_L2_PROMOTION_L2_128B);
    make_map(enc, &kmap, d_in[1], kDh, (uint64_t)kB * kHkv * kSk, 64, kChunkKeys, CU_TENSOR_MAP_SWIZZLE_128B,
             CU_TENSOR_MAP_L2_PROMOTION_L2_256B);
    make_map(enc, &vmap, d_in[2], kDh, (uint64_t)kB * kHkv * kSk, 64, kChunkKeys, CU_TENSOR_MAP_SWIZZLE_128B,
             CU_TENSOR_MAP_L2_PROMOTION_L2_256B);
    make_map(enc, &womap, d_in[4], kD, kNQ, kCols3, 128, CU_TENSOR_MAP_SWIZZLE_NONE,
             CU_TENSOR_MAP_L2_PROMOTION_L2_128B);
    make_map(enc, &w2map, d_in[7], kD, kF, kCols3, 144, CU_TENSOR_MAP_SWIZZLE_NONE,
             CU_TENSOR_MAP_L2_PROMOTION_L2_128B);
    fused_decode_kernel<<<kCTAs, 288, SMEM_BYTES>>>(kmap, vmap, womap, w2map, wqmap, w1map,
                                                    (const __nv_bfloat16*)d_in[0], (__nv_bfloat16*)d_out);
}
```

```cpp
#include <cuda_runtime.h>
#include <cuda_bf16.h>
#include <cuda.h>
#include <stdint.h>

namespace {

constexpr int kB = 4, kD = 576, kHkv = 16, kSk = 4096, kDh = 128, kWin = 1024, kF = 4608;
constexpr int kNQ = 4096;
constexpr int kGroups = 16, kRanks = 8, kCTAs = 128;
constexpr int kRows1 = 72;
constexpr int kQCols = 256, kHCols = 288;
constexpr int kCols3 = 72;
constexpr int kChunkKeys = 64;
constexpr int kFinalCons = 72;

constexpr int kSlotBytes = 16384;
constexpr int OFF_KV = 0;
constexpr int STR_W3 = 144;
constexpr int BOX_WQ = 144 * 64;
constexpr int BOX_W1 = 144 * 80;
constexpr int OFF_A = 8 * kSlotBytes;
constexpr int SZ_A = 4 * BOX_WQ;
constexpr int OFF_B = OFF_A + SZ_A;
constexpr int SZ_B = 4 * BOX_W1;
constexpr int OFF_XN = OFF_B + SZ_B;
constexpr int OFF_Q = OFF_XN + 4 * 584 * 2;
constexpr int OFF_H = OFF_Q + 544;
constexpr int OFF_O = OFF_H + 4 * 296 * 2;
constexpr int OFF_P = OFF_O + 4 * 264 * 2;
constexpr int OFF_ML = OFF_P + 2 * 520 * 2;
constexpr int OFF_STG = OFF_ML + 128;
constexpr int OFF_BAR = OFF_STG + 1024;
constexpr int SMEM_USED = OFF_BAR + 288;
constexpr int SMEM_BYTES = SMEM_USED + 1024;

static_assert(OFF_A % 128 == 0 && OFF_B % 128 == 0, "align");
static_assert(OFF_BAR % 8 == 0 && OFF_STG % 16 == 0, "align");
static_assert(SMEM_BYTES <= 232448, "smem");

__device__ __align__(128) uint32_t g_qx[kGroups * kB * kQCols];
__device__ __align__(128) uint32_t g_hx[kGroups * kB * kHCols];
__device__ __align__(128) uint32_t g_opart[kGroups * kB * 2 * 2 * 136];
__device__ __align__(128) uint32_t g_fpart[kFinalCons * 2 * kGroups * 32];
__device__ uint32_t g_epoch;

constexpr int kSpinLimit = 1 << 22;
#define INIT_VARIANT 5
#define KWINDOW 3
constexpr int kWindow = KWINDOW;

#define ORDER 2
#define G_AT 3
#define G_FIRST (ORDER == 1 || ORDER == 2 || ORDER == 4)
__host__ __device__ constexpr int order_at(int n) { return n < 12 ? n : (n < 14 ? n + 8 : (n < 22 ? n - 2 : n)); }
#define ORDER_AT(n) order_at(n)

#define TS(k)
#define TS2(k)

__device__ __forceinline__ uint32_t smem_u32(const void* p) {
    return (uint32_t)__cvta_generic_to_shared(p);
}
__device__ __forceinline__ void mbar_init(uint32_t bar, uint32_t count) {
    asm volatile("mbarrier.init.shared::cta.b64 [%0], %1;" ::"r"(bar), "r"(count) : "memory");
}
__device__ __forceinline__ void mbar_expect_tx(uint32_t bar, uint32_t bytes) {
    asm volatile("mbarrier.arrive.expect_tx.shared::cta.b64 _, [%0], %1;" ::"r"(bar), "r"(bytes) : "memory");
}
__device__ __forceinline__ void mbar_arrive(uint32_t bar) {
    asm volatile("mbarrier.arrive.shared::cta.b64 _, [%0];" ::"r"(bar) : "memory");
}
__device__ __forceinline__ bool mbar_try_wait(uint32_t bar, uint32_t parity) {
    uint32_t ok;
    asm volatile(
        "{\n .reg .pred p;\n mbarrier.try_wait.parity.shared::cta.b64 p, [%1], %2;\n selp.u32 %0, 1, 0, p;\n}"
        : "=r"(ok)
        : "r"(bar), "r"(parity)
        : "memory");
    return ok != 0;
}
__device__ __forceinline__ void mbar_wait(uint32_t bar, uint32_t parity) {
    for (int i = 0; i < kSpinLimit; i++) {
        if (mbar_try_wait(bar, parity)) break;
    }
}
__device__ __forceinline__ void bulk_g2s(uint32_t dst, const void* src, uint32_t bytes, uint32_t bar) {
    asm volatile(
        "cp.async.bulk.shared::cluster.global.mbarrier::complete_tx::bytes [%0], [%1], %2, [%3];" ::"r"(dst),
        "l"(src), "r"(bytes), "r"(bar)
        : "memory");
}
__device__ __forceinline__ void tma_2d_ef(uint32_t dst, const CUtensorMap* map, int c0, int c1, uint32_t bar) {
    uint64_t pol;
    asm volatile("createpolicy.fractional.L2::evict_first.b64 %0, 1.0;" : "=l"(pol));
    asm volatile(
        "cp.async.bulk.tensor.2d.shared::cluster.global.mbarrier::complete_tx::bytes.L2::cache_hint [%0], [%1, {%3, %4}], [%2], %5;" ::"r"(dst),
        "l"(map), "r"(bar), "r"(c0), "r"(c1), "l"(pol)
        : "memory");
}
__device__ __forceinline__ void tma_2d(uint32_t dst, const CUtensorMap* map, int c0, int c1, uint32_t bar) {
    asm volatile(
        "cp.async.bulk.tensor.2d.shared::cluster.global.mbarrier::complete_tx::bytes [%0], [%1, {%3, %4}], [%2];" ::"r"(dst),
        "l"(map), "r"(bar), "r"(c0), "r"(c1)
        : "memory");
}
__device__ __forceinline__ void ldsm_x4(uint32_t addr, uint32_t& r0, uint32_t& r1, uint32_t& r2, uint32_t& r3) {
    asm volatile("ldmatrix.sync.aligned.m8n8.x4.shared.b16 {%0,%1,%2,%3}, [%4];"
                 : "=r"(r0), "=r"(r1), "=r"(r2), "=r"(r3)
                 : "r"(addr)
                 : "memory");
}
__device__ __forceinline__ void ldsm_x4_t(uint32_t addr, uint32_t& r0, uint32_t& r1, uint32_t& r2, uint32_t& r3) {
    asm volatile("ldmatrix.sync.aligned.m8n8.x4.trans.shared.b16 {%0,%1,%2,%3}, [%4];"
                 : "=r"(r0), "=r"(r1), "=r"(r2), "=r"(r3)
                 : "r"(addr)
                 : "memory");
}
__device__ __forceinline__ void ldsm_x2_t(uint32_t addr, uint32_t& r0, uint32_t& r1) {
    asm volatile("ldmatrix.sync.aligned.m8n8.x2.trans.shared.b16 {%0,%1}, [%2];"
                 : "=r"(r0), "=r"(r1)
                 : "r"(addr)
                 : "memory");
}
__device__ __forceinline__ void mma16816(float (&c)[4], uint32_t a0, uint32_t a1, uint32_t a2, uint32_t a3,
                                         uint32_t b0, uint32_t b1) {
    asm volatile(
        "mma.sync.aligned.m16n8k16.row.col.f32.bf16.bf16.f32 {%0,%1,%2,%3}, {%4,%5,%6,%7}, {%8,%9}, {%0,%1,%2,%3};"
        : "+f"(c[0]), "+f"(c[1]), "+f"(c[2]), "+f"(c[3])
        : "r"(a0), "r"(a1), "r"(a2), "r"(a3), "r"(b0), "r"(b1));
}
__device__ __forceinline__ void mma1688(float (&c)[4], uint32_t a0, uint32_t a1, uint32_t b0) {
    asm volatile("mma.sync.aligned.m16n8k8.row.col.f32.bf16.bf16.f32 {%0,%1,%2,%3}, {%4,%5}, {%6}, {%0,%1,%2,%3};"
                 : "+f"(c[0]), "+f"(c[1]), "+f"(c[2]), "+f"(c[3])
                 : "r"(a0), "r"(a1), "r"(b0));
}
__device__ __forceinline__ void bar_cons() { asm volatile("bar.sync 1, 256;" ::: "memory"); }

__device__ __forceinline__ float bfr(float x) { return __bfloat162float(__float2bfloat16_rn(x)); }
__device__ __forceinline__ uint32_t pack_bf16(float lo, float hi) {
    __nv_bfloat162 v = __floats2bfloat162_rn(lo, hi);
    return *reinterpret_cast<uint32_t*>(&v);
}
__device__ __forceinline__ uint32_t tagw(float v, uint32_t flag) { return (__float_as_uint(v) & ~1u) | flag; }
__device__ __forceinline__ void st_word(uint32_t* p, uint32_t v) {
    asm volatile("st.relaxed.gpu.global.u32 [%0], %1;" ::"l"(p), "r"(v) : "memory");
}
__device__ __forceinline__ void st_word2(uint32_t* p, uint32_t v0, uint32_t v1) {
    asm volatile("st.relaxed.gpu.global.v2.u32 [%0], {%1,%2};" ::"l"(p), "r"(v0), "r"(v1) : "memory");
}
__device__ __forceinline__ void st_word4(uint32_t* p, uint32_t v) {
    asm volatile("st.relaxed.gpu.global.v4.u32 [%0], {%1,%1,%1,%1};" ::"l"(p), "r"(v) : "memory");
}
__device__ __forceinline__ void st_word4v(uint32_t* p, uint32_t a, uint32_t b, uint32_t c, uint32_t d) {
    asm volatile("st.relaxed.gpu.global.v4.u32 [%0], {%1,%2,%3,%4};" ::"l"(p), "r"(a), "r"(b), "r"(c), "r"(d) : "memory");
}
__device__ __forceinline__ uint32_t ld_word(const uint32_t* p) {
    uint32_t v;
    asm volatile("ld.relaxed.gpu.global.u32 %0, [%1];" : "=r"(v) : "l"(p) : "memory");
    return v;
}
__device__ __forceinline__ uint2 ld_word2(const uint32_t* p) {
    uint2 v;
    asm volatile("ld.relaxed.gpu.global.v2.u32 {%0,%1}, [%2];" : "=r"(v.x), "=r"(v.y) : "l"(p) : "memory");
    return v;
}
__device__ __forceinline__ uint4 ld_word4(const uint32_t* p) {
    uint4 v;
    asm volatile("ld.relaxed.gpu.global.v4.u32 {%0,%1,%2,%3}, [%4];"
                 : "=r"(v.x), "=r"(v.y), "=r"(v.z), "=r"(v.w)
                 : "l"(p)
                 : "memory");
    return v;
}
__device__ __forceinline__ float silu_f(float x) { return x / (1.0f + __expf(-x)); }

template <int KSTEPS, int ASTRIDE>
__device__ __forceinline__ void gemv3_tile(uint32_t wbuf, const __nv_bfloat16* act, int nt, int lane, float (&c)[4]) {
    const int gid = lane >> 2, tig = lane & 3, lm_i = lane & 7, lm_j = lane >> 3;
    const uint32_t wb = wbuf + (8 * lm_j + lm_i) * STR_W3 + nt * 16;
    const __nv_bfloat16* ap = act + (gid & 3) * ASTRIDE + 2 * tig;
    float acc[4][4];
#pragma unroll
    for (int i = 0; i < 4; i++) acc[i][0] = acc[i][1] = acc[i][2] = acc[i][3] = 0.f;
#pragma unroll
    for (int kk = 0; kk < KSTEPS / 2; kk++) {
        uint32_t b0, b1, b2, b3;
        ldsm_x4_t(wb + kk * 32 * STR_W3, b0, b1, b2, b3);
        uint32_t a0 = *reinterpret_cast<const uint32_t*>(ap + 32 * kk);
        uint32_t a2 = *reinterpret_cast<const uint32_t*>(ap + 32 * kk + 8);
        uint32_t a4 = *reinterpret_cast<const uint32_t*>(ap + 32 * kk + 16);
        uint32_t a6 = *reinterpret_cast<const uint32_t*>(ap + 32 * kk + 24);
        if (gid >= 4) a0 = a2 = a4 = a6 = 0u;
        mma16816(acc[(2 * kk) & 3], a0, 0u, a2, 0u, b0, b1);
        mma16816(acc[(2 * kk + 1) & 3], a4, 0u, a6, 0u, b2, b3);
    }
    c[0] = (acc[0][0] + acc[1][0]) + (acc[2][0] + acc[3][0]);
    c[1] = (acc[0][1] + acc[1][1]) + (acc[2][1] + acc[3][1]);
    c[2] = c[3] = 0.f;
}

__global__ void __launch_bounds__(288, 1)
fused_decode_kernel(const __grid_constant__ CUtensorMap kmap, const __grid_constant__ CUtensorMap vmap,
                    const __grid_constant__ CUtensorMap womap, const __grid_constant__ CUtensorMap w2map,
                    const __grid_constant__ CUtensorMap wqmap, const __grid_constant__ CUtensorMap w1map,
                    const __nv_bfloat16* __restrict__ x, __nv_bfloat16* __restrict__ out) {
    extern __shared__ uint8_t smem_raw[];
    const uint32_t raw_u32 = smem_u32(smem_raw);
    const uint32_t sbase = (raw_u32 + 1023u) & ~1023u;
    uint8_t* sgen = smem_raw + (sbase - raw_u32);

    const int tid = threadIdx.x, warp = tid >> 5, lane = tid & 31;
    const int cta = blockIdx.x;
    const int g = cta >> 3, r = cta & 7;
    const int b = r >> 1, half = r & 1;

    const uint32_t bar_full = sbase + OFF_BAR;
    const uint32_t bar_empty = sbase + OFF_BAR + 24 * 8;
    const uint32_t bar_s1 = sbase + OFF_BAR + 32 * 8;

    const int kv_row0 = (b * kHkv + g) * kSk + (kSk - kWin) + half * 512;
    const int hst = (36 * r) >> 3;
    const int hcnt = ((36 * (r + 1)) >> 3) - hst;

    if (warp == 8) {
        if (lane == 0) {
            TS(0);
            for (int i = 0; i < 4; i++) mbar_init(bar_full + 8 * i, 1);
            asm volatile("fence.mbarrier_init.release.cluster;" ::: "memory");
            asm volatile("fence.proxy.async.shared::cta;" ::: "memory");
        }
        __syncwarp();
        if (lane == 0) TS2(31);
#pragma unroll
        for (int n = 0; n < 24; n++) {
            const int u = ORDER_AT(n);
            if (n == 3) {
                if (lane == 0) {
                    for (int i = 4; i < 32; i++) mbar_init(bar_full + 8 * i, 1);
                    mbar_init(bar_s1, 8);
                    asm volatile("fence.mbarrier_init.release.cluster;" ::: "memory");
                    asm volatile("fence.proxy.async.shared::cta;" ::: "memory");
                }
                __syncwarp();
                asm volatile("bar.arrive 2, 288;" ::: "memory");
            }
            if (n >= kWindow) mbar_wait(bar_full + 8 * ORDER_AT(n >= kWindow ? n - kWindow : 0), 0);
            const uint32_t bar = bar_full + 8 * u;
            if (u < 2) {
                if (lane == 0) {
                    mbar_expect_tx(bar, 2 * BOX_WQ);
                    tma_2d(sbase + OFF_A + (2 * u) * BOX_WQ, &wqmap, kQCols * g + 32 * r, 144 * (2 * u), bar);
                    tma_2d(sbase + OFF_A + (2 * u + 1) * BOX_WQ, &wqmap, kQCols * g + 32 * r, 144 * (2 * u + 1), bar);
                }
            } else if (u < 4) {
                if (lane == 0) {
                    mbar_expect_tx(bar, 2 * BOX_W1);
                    tma_2d(sbase + OFF_B + (2 * u - 4) * BOX_W1, &w1map, kHCols * g + 8 * hst, 144 * (2 * u - 4), bar);
                    tma_2d(sbase + OFF_B + (2 * u - 3) * BOX_W1, &w1map, kHCols * g + 8 * hst, 144 * (2 * u - 3), bar);
                }
            } else if (u < 20) {
                const int c = (u - 4) & 7;
                if (u >= 12) mbar_wait(bar_empty + 8 * c, 0);
                if (lane == 0) {
                    const CUtensorMap* mp = u >= 12 ? &vmap : &kmap;
                    mbar_expect_tx(bar, kSlotBytes);
                    tma_2d_ef(sbase + OFF_KV + c * kSlotBytes, mp, 0, kv_row0 + kChunkKeys * c, bar);
                    tma_2d_ef(sbase + OFF_KV + c * kSlotBytes + 8192, mp, 64, kv_row0 + kChunkKeys * c, bar);
                }
            } else if (u < 22) {
                mbar_wait(bar_s1, 0);
                if (lane == 0) {
                    mbar_expect_tx(bar, 144 * STR_W3);
                    tma_2d(sbase + OFF_B + (u - 20) * 144 * STR_W3, &w2map, kCols3 * r, kHCols * g + 144 * (u - 20), bar);
                }
            } else {
                mbar_wait(bar_s1, 0);
                if (lane == 0) {
                    mbar_expect_tx(bar, 128 * STR_W3);
                    tma_2d(sbase + OFF_A + (u - 22) * 128 * STR_W3, &womap, kCols3 * r, kQCols * g + 128 * (u - 22), bar);
                }
            }
            if (lane == 0) TS2(n);
            __syncwarp();
        }
        asm volatile("bar.sync 3, 288;" ::: "memory");
        mbar_wait(bar_full + 8 * 22, 0);
        mbar_wait(bar_full + 8 * 23, 0);
        const uint32_t flag_p = *reinterpret_cast<volatile uint32_t*>(sgen + OFF_BAR + 280);
        {
            float c[4];
            gemv3_tile<16, 264>(sbase + OFF_A, reinterpret_cast<const __nv_bfloat16*>(sgen + OFF_O), 8, lane, c);
            if ((lane >> 2) < 4)
                st_word2(g_fpart + (size_t)(((r * 9 + 8) * 2 + 0) * kGroups + g) * 32 + (lane >> 2) * 8 + 2 * (lane & 3),
                         tagw(c[0], flag_p), tagw(c[1], flag_p));
        }
        return;
    }

    uint32_t epoch;
    asm volatile("ld.relaxed.gpu.global.u32 %0, [%1];" : "=r"(epoch) : "l"(&g_epoch) : "memory");
    uint32_t xw[9];
    if (warp < 4) {
        const uint32_t* xr = reinterpret_cast<const uint32_t*>(x + warp * kD);
#pragma unroll
        for (int i = 0; i < 9; i++) xw[i] = __ldg(xr + lane + 32 * i);
    }
    float x_fin[4] = {0.f, 0.f, 0.f, 0.f};
    if (cta < kFinalCons && tid < 8) {
        const int rc = cta / 9, ntc = cta - 9 * rc;
        const uint2 xv = __ldg(reinterpret_cast<const uint2*>(x + (tid >> 1) * kD + kCols3 * rc + 8 * ntc + (tid & 1) * 4));
        x_fin[0] = __uint_as_float(xv.x << 16);
        x_fin[1] = __uint_as_float(xv.x & 0xffff0000u);
        x_fin[2] = __uint_as_float(xv.y << 16);
        x_fin[3] = __uint_as_float(xv.y & 0xffff0000u);
    }
    const uint32_t flag = (epoch + 1u) & 1u;

    __nv_bfloat16* xn_s = reinterpret_cast<__nv_bfloat16*>(sgen + OFF_XN);
    __nv_bfloat16* q_s = reinterpret_cast<__nv_bfloat16*>(sgen + OFF_Q);
    __nv_bfloat16* h_s = reinterpret_cast<__nv_bfloat16*>(sgen + OFF_H);
    __nv_bfloat16* o_s = reinterpret_cast<__nv_bfloat16*>(sgen + OFF_O);
    __nv_bfloat16* p_s = reinterpret_cast<__nv_bfloat16*>(sgen + OFF_P);
    float* ml_s = reinterpret_cast<float*>(sgen + OFF_ML);

    if (tid == 0) *reinterpret_cast<volatile uint32_t*>(sgen + OFF_BAR + 280) = flag;
    {
        const uint32_t inv = flag ^ 1u;
        if (tid < 32) {
            st_word4(g_qx + (size_t)(g * kB + (tid >> 3)) * kQCols + 32 * r + 4 * (tid & 7), inv);
        } else if (tid < 32 + 40) {
            {
            const int i = tid - 32, bb = i / 10, c4 = i - bb * 10;
            if (c4 < 2 * hcnt) st_word4(g_hx + (size_t)(g * kB + bb) * kHCols + 8 * hst + 4 * c4, inv);
            }
        } else if (tid >= 96 && tid < 96 + 68) {
            st_word4(g_opart + (size_t)((g * kB + b) * 2 + half) * 272 + 4 * (tid - 96), inv);
        } else if (tid >= 184) {
            const int i = tid - 184;
            const int nt = i >> 3, c4 = i & 7;
            st_word4(g_fpart + (size_t)(((r * 9 + nt) * 2 + 0) * kGroups + g) * 32 + 4 * c4, inv);
        }
    }

    if (warp < 4) {
        float v[18];
        float sum = 0.f;
#pragma unroll
        for (int i = 0; i < 9; i++) {
            v[2 * i] = __uint_as_float(xw[i] << 16);
            v[2 * i + 1] = __uint_as_float(xw[i] & 0xffff0000u);
            sum += v[2 * i] + v[2 * i + 1];
        }
#pragma unroll
        for (int o = 16; o > 0; o >>= 1) sum += __shfl_xor_sync(0xffffffffu, sum, o);
        const float mean = sum * (1.0f / kD);
        float sq = 0.f;
#pragma unroll
        for (int i = 0; i < 18; i++) {
            float d = v[i] - mean;
            sq += d * d;
        }
#pragma unroll
        for (int o = 16; o > 0; o >>= 1) sq += __shfl_xor_sync(0xffffffffu, sq, o);
        const float m_bf = bfr(mean);
        const float v_bf = bfr(sq * (1.0f / kD));
        const float den = bfr(sqrtf(bfr(v_bf + 1e-5f)));
#pragma unroll
        for (int i = 0; i < 9; i++) {
            const float a0 = bfr(v[2 * i] - m_bf) / den;
            const float a1 = bfr(v[2 * i + 1] - m_bf) / den;
            *reinterpret_cast<uint32_t*>(xn_s + warp * 584 + 2 * (lane + 32 * i)) = pack_bf16(a0, a1);
        }
    }
    asm volatile("bar.sync 2, 288;" ::: "memory");
    if (tid == 0) TS(1);

    const int gid = lane >> 2, tig = lane & 3;
    const int lm_i = lane & 7, lm_j = lane >> 3;

    {
        const __nv_bfloat16* ap = xn_s + (gid & 3) * 584 + 2 * tig;
#pragma unroll 1
        for (int job = warp; job < 9; job += 8) {
            const bool isq = job < 4;
            const int nt = isq ? job : job - 4;
            if (!isq && nt >= hcnt) break;
            float acc[4][4];
#pragma unroll
            for (int i = 0; i < 4; i++) acc[i][0] = acc[i][1] = acc[i][2] = acc[i][3] = 0.f;
#pragma unroll 1
            for (int bx = 0; bx < 4; bx++) {
                if ((bx & 1) == 0) mbar_wait(bar_full + 8 * ((isq ? 0 : 2) + (bx >> 1)), 0);
#pragma unroll
                for (int kk = 0; kk < 5; kk++) {
                    const int row = 32 * kk + 8 * lm_j + lm_i;
                    uint32_t addr;
                    if (isq)
                        addr = sbase + OFF_A + bx * BOX_WQ + row * 64 + ((nt ^ ((row >> 1) & 3)) << 4);
                    else
                        addr = sbase + OFF_B + bx * BOX_W1 + row * 80 + nt * 16;
                    const int k0 = 144 * bx + 32 * kk;
                    uint32_t a0 = *reinterpret_cast<const uint32_t*>(ap + k0);
                    uint32_t a2 = *reinterpret_cast<const uint32_t*>(ap + k0 + 8);
                    if (gid >= 4) a0 = a2 = 0u;
                    if (kk < 4) {
                        uint32_t b0, b1, b2, b3;
                        ldsm_x4_t(addr, b0, b1, b2, b3);
                        uint32_t a4 = *reinterpret_cast<const uint32_t*>(ap + k0 + 16);
                        uint32_t a6 = *reinterpret_cast<const uint32_t*>(ap + k0 + 24);
                        if (gid >= 4) a4 = a6 = 0u;
                        mma16816(acc[(2 * kk) & 3], a0, 0u, a2, 0u, b0, b1);
                        mma16816(acc[(2 * kk + 1) & 3], a4, 0u, a6, 0u, b2, b3);
                    } else {
                        uint32_t b0, b1;
                        ldsm_x2_t(addr, b0, b1);
                        mma16816(acc[0], a0, 0u, a2, 0u, b0, b1);
                    }
                }
            }
            float c0 = (acc[0][0] + acc[1][0]) + (acc[2][0] + acc[3][0]);
            float c1 = (acc[0][1] + acc[1][1]) + (acc[2][1] + acc[3][1]);
            if (gid < 4) {
                if (isq) {
                    const uint32_t pk = pack_bf16(c0, c1);
                    st_word2(g_qx + (size_t)(g * kB + gid) * kQCols + 32 * r + 8 * nt + 2 * tig, (pk << 16) | flag,
                             (pk & 0xffff0000u) | flag);
                } else {
                    const uint32_t pk = pack_bf16(silu_f(bfr(c0)), silu_f(bfr(c1)));
                    st_word2(g_hx + (size_t)(g * kB + gid) * kHCols + 8 * (hst + nt) + 2 * tig, (pk << 16) | flag,
                             (pk & 0xffff0000u) | flag);
                }
            }
        }
        if (tid == 0) TS(3);
    }
    __syncwarp();
    if (lane == 0) mbar_arrive(bar_s1);

    if (tid < 64) {
        const uint32_t* src = g_qx + (size_t)(g * kB + b) * kQCols + 4 * tid;
        uint4 w;
        for (int it = 0; it < kSpinLimit; it++) {
            w = ld_word4(src);
            const uint32_t bad = (w.x ^ flag) | (w.y ^ flag) | (w.z ^ flag) | (w.w ^ flag);
            if (!(bad & 1u)) break;
        }
        uint2 pk;
        pk.x = (w.x >> 16) | (w.y & 0xffff0000u);
        pk.y = (w.z >> 16) | (w.w & 0xffff0000u);
        *reinterpret_cast<uint2*>(q_s + (tid >> 5) * 136 + 4 * (tid & 31)) = pk;
    }
    bar_cons();
    if (tid == 0) TS(4);

    float sc[8][2];
    {
        const uint32_t slot = sbase + OFF_KV + warp * kSlotBytes;
        uint32_t qa[16];
#pragma unroll
        for (int j = 0; j < 8; j++) {
            qa[2 * j] = gid < 2 ? *reinterpret_cast<const uint32_t*>(q_s + gid * 136 + 16 * j + 2 * tig) : 0u;
            qa[2 * j + 1] = gid < 2 ? *reinterpret_cast<const uint32_t*>(q_s + gid * 136 + 16 * j + 8 + 2 * tig) : 0u;
        }
        mbar_wait(bar_full + 8 * (4 + warp), 0);
        if (tid == 0) TS(5);
        if (tid == 224) TS(7);
        float mx = -INFINITY;
        const float scale = 0.08838834764831845f;
#pragma unroll
        for (int nt = 0; nt < 8; nt++) {
            float acc[4] = {0.f, 0.f, 0.f, 0.f};
#pragma unroll
            for (int kk = 0; kk < 4; kk++) {
                const int cg = 4 * kk + lm_j;
                const uint32_t addr =
                    slot + (cg >> 3) * 8192 + (8 * nt + lm_i) * 128 + (((cg & 7) ^ lm_i) << 4);
                uint32_t b0, b1, b2, b3;
                ldsm_x4(addr, b0, b1, b2, b3);
                mma16816(acc, qa[4 * kk], 0u, qa[4 * kk + 1], 0u, b0, b1);
                mma16816(acc, qa[4 * kk + 2], 0u, qa[4 * kk + 3], 0u, b2, b3);
            }
            sc[nt][0] = bfr(bfr(acc[0]) * scale);
            sc[nt][1] = bfr(bfr(acc[1]) * scale);
            mx = fmaxf(mx, fmaxf(sc[nt][0], sc[nt][1]));
        }
        __syncwarp();
        if (lane == 0) mbar_arrive(bar_empty + 8 * warp);
        mx = fmaxf(mx, __shfl_xor_sync(0xffffffffu, mx, 1));
        mx = fmaxf(mx, __shfl_xor_sync(0xffffffffu, mx, 2));
        if (lane == 0 || lane == 4) ml_s[(lane >> 2) * 8 + warp] = mx;
    }

    {
        for (int idx = tid; idx < kB * kHCols / 4; idx += 256) {
            const uint32_t* src = g_hx + (size_t)g * kB * kHCols + 4 * idx;
            uint4 w;
            for (int it = 0; it < kSpinLimit; it++) {
                w = ld_word4(src);
                const uint32_t bad = (w.x ^ flag) | (w.y ^ flag) | (w.z ^ flag) | (w.w ^ flag);
                if (!(bad & 1u)) break;
            }
            const int bb = idx / 72, c4 = idx - bb * 72;
            uint2 pk;
            pk.x = (w.x >> 16) | (w.y & 0xffff0000u);
            pk.y = (w.z >> 16) | (w.w & 0xffff0000u);
            *reinterpret_cast<uint2*>(h_s + bb * 296 + 4 * c4) = pk;
        }
        if (tid == 0) TS(10);
    }
    bar_cons();

    {
        const int hh = gid & 1;
        float M = ml_s[hh * 8];
#pragma unroll
        for (int w = 1; w < 8; w++) M = fmaxf(M, ml_s[hh * 8 + w]);
        const float l2e = 1.4426950408889634f;
        float lsum = 0.f;
#pragma unroll
        for (int nt = 0; nt < 8; nt++) {
            const float p0 = exp2f((sc[nt][0] - M) * l2e);
            const float p1 = exp2f((sc[nt][1] - M) * l2e);
            lsum += p0 + p1;
            if (gid < 2) *reinterpret_cast<uint32_t*>(p_s + gid * 520 + 64 * warp + 8 * nt + 2 * tig) = pack_bf16(p0, p1);
        }
        lsum += __shfl_xor_sync(0xffffffffu, lsum, 1);
        lsum += __shfl_xor_sync(0xffffffffu, lsum, 2);
        if (lane == 0 || lane == 4) ml_s[16 + (lane >> 2) * 8 + warp] = lsum;
    }
    bar_cons();

    {
        float oc[2][4] = {{0.f, 0.f, 0.f, 0.f}, {0.f, 0.f, 0.f, 0.f}};
        const int cg = 2 * warp + (lm_j & 1);
        const uint32_t vbase = sbase + OFF_KV + (cg >> 3) * 8192 + ((lm_j >> 1) * 8 + lm_i) * 128 + (((cg & 7) ^ lm_i) << 4);
        const __nv_bfloat16* pp = p_s + (gid & 1) * 520 + 2 * tig;
#pragma unroll 1
        for (int c = 0; c < 8; c++) {
            uint32_t pb[8];
#pragma unroll
            for (int j = 0; j < 8; j++) {
                pb[j] = *reinterpret_cast<const uint32_t*>(pp + 64 * c + 8 * j);
                if (gid >= 2) pb[j] = 0u;
            }
            if (c == G_AT) {
                mbar_wait(bar_full + 8 * 20, 0);
                mbar_wait(bar_full + 8 * 21, 0);
                for (int nt = 7 - warp; nt < 9; nt += 8) {
                    float cc[4];
                    gemv3_tile<18, 296>(sbase + OFF_B, h_s, nt, lane, cc);
                    if (gid < 4)
                        st_word2(g_fpart + (size_t)(((r * 9 + nt) * 2 + 1) * kGroups + g) * 32 + gid * 8 + 2 * tig,
                                 tagw(cc[0], flag), tagw(cc[1], flag));
                }
            }
            mbar_wait(bar_full + 8 * (12 + c), 0);
            if (tid == 0 && c == 0) TS(6);
            if (tid == 0 && c == 7) TS(8);
#pragma unroll
            for (int ks = 0; ks < 4; ks++) {
                uint32_t a0, a1, a2, a3;
                ldsm_x4_t(vbase + c * kSlotBytes + ks * 16 * 128, a0, a1, a2, a3);
                mma16816(oc[ks & 1], a0, a1, a2, a3, pb[2 * ks], pb[2 * ks + 1]);
            }
        }
        uint32_t* od = g_opart + (size_t)((g * kB + b) * 2 + half) * 272;
        float* stg = reinterpret_cast<float*>(sgen + OFF_STG) + warp * 32;
        if (tig == 0) {
            stg[gid] = oc[0][0] + oc[1][0];
            stg[16 + gid] = oc[0][1] + oc[1][1];
            stg[gid + 8] = oc[0][2] + oc[1][2];
            stg[16 + gid + 8] = oc[0][3] + oc[1][3];
        }
        __syncwarp();
        if (lane < 8) {
            const float4 v = *reinterpret_cast<const float4*>(stg + 4 * lane);
            st_word4v(od + (lane >> 2) * 128 + 16 * warp + 4 * (lane & 3), tagw(v.x, flag), tagw(v.y, flag),
                      tagw(v.z, flag), tagw(v.w, flag));
        } else if (warp == 0 && lane == 8) {
            float M0 = ml_s[0], L0 = ml_s[16], M1 = ml_s[8], L1 = ml_s[24];
#pragma unroll
            for (int w = 1; w < 8; w++) {
                M0 = fmaxf(M0, ml_s[w]);
                L0 += ml_s[16 + w];
                M1 = fmaxf(M1, ml_s[8 + w]);
                L1 += ml_s[24 + w];
            }
            st_word4v(od + 256, tagw(M0, flag), tagw(L0, flag), tagw(M1, flag), tagw(L1, flag));
        }
    }
    if (tid == 0) TS(13);

    {
        const int bb = tid >> 6, head = (tid >> 5) & 1, d4 = tid & 31;
        const uint32_t* src = g_opart + (size_t)((g * kB + bb) * 2) * 272;
        uint4 wa, wb2, sa, sb;
        if (tid == 0) TS(18);
        for (int it = 0; it < kSpinLimit; it++) {
            wa = ld_word4(src + head * 128 + 4 * d4);
            wb2 = ld_word4(src + 272 + head * 128 + 4 * d4);
            sa = ld_word4(src + 256);
            sb = ld_word4(src + 272 + 256);
            const uint32_t bad = (wa.x ^ flag) | (wa.y ^ flag) | (wa.z ^ flag) | (wa.w ^ flag) | (wb2.x ^ flag) |
                                 (wb2.y ^ flag) | (wb2.z ^ flag) | (wb2.w ^ flag) | (sa.x ^ flag) | (sa.y ^ flag) |
                                 (sa.z ^ flag) | (sa.w ^ flag) | (sb.x ^ flag) | (sb.y ^ flag) | (sb.z ^ flag) |
                                 (sb.w ^ flag);
            if (!(bad & 1u)) break;
        }
        if (tid == 0) TS(19);
        if (tid == 255) TS(20);
        const float m0 = __uint_as_float(head ? sa.z : sa.x), l0 = __uint_as_float(head ? sa.w : sa.y);
        const float m1 = __uint_as_float(head ? sb.z : sb.x), l1 = __uint_as_float(head ? sb.w : sb.y);
        const float MM = fmaxf(m0, m1);
        const float e0 = exp2f((m0 - MM) * 1.4426950408889634f), e1 = exp2f((m1 - MM) * 1.4426950408889634f);
        const float inv = 1.0f / (e0 * l0 + e1 * l1);
        const float f0 = e0 * inv, f1 = e1 * inv;
        uint2 pk;
        pk.x = pack_bf16(f0 * __uint_as_float(wa.x) + f1 * __uint_as_float(wb2.x),
                         f0 * __uint_as_float(wa.y) + f1 * __uint_as_float(wb2.y));
        pk.y = pack_bf16(f0 * __uint_as_float(wa.z) + f1 * __uint_as_float(wb2.z),
                         f0 * __uint_as_float(wa.w) + f1 * __uint_as_float(wb2.w));
        *reinterpret_cast<uint2*>(o_s + bb * 264 + head * 128 + 4 * d4) = pk;
    }
    asm volatile("bar.sync 3, 288;" ::: "memory");
    if (tid == 0) TS(9);
    mbar_wait(bar_full + 8 * 22, 0);
    mbar_wait(bar_full + 8 * 23, 0);
    if (tid == 0) TS(14);

    {
        float c[4];
        gemv3_tile<16, 264>(sbase + OFF_A, o_s, warp, lane, c);
        if (gid < 4)
            st_word2(g_fpart + (size_t)(((r * 9 + warp) * 2 + 0) * kGroups + g) * 32 + gid * 8 + 2 * tig,
                     tagw(c[0], flag), tagw(c[1], flag));
    }
    if (tid == 0) TS(15);

    if (cta < kFinalCons && warp == 0) {
        const int gh = lane >> 4, which = (lane >> 3) & 1, bc = lane & 7;
        const uint32_t* src = g_fpart + (size_t)cta * 1024 + (which * kGroups + gh * 8) * 32 + bc * 4;
        uint4 w[8];
        for (int it = 0; it < kSpinLimit; it++) {
            uint32_t bad = 0;
#pragma unroll
            for (int i = 0; i < 8; i++) {
                w[i] = ld_word4(src + i * 32);
                bad |= (w[i].x ^ flag) | (w[i].y ^ flag) | (w[i].z ^ flag) | (w[i].w ^ flag);
            }
            if (!__any_sync(0xffffffffu, bad & 1u)) break;
        }
        if (tid == 0) TS(16);
        float v[4] = {0.f, 0.f, 0.f, 0.f};
#pragma unroll
        for (int i = 0; i < 8; i++) {
            v[0] += __uint_as_float(w[i].x);
            v[1] += __uint_as_float(w[i].y);
            v[2] += __uint_as_float(w[i].z);
            v[3] += __uint_as_float(w[i].w);
        }
        float gsum[4];
#pragma unroll
        for (int j = 0; j < 4; j++) {
            v[j] += __shfl_xor_sync(0xffffffffu, v[j], 16);
            gsum[j] = __shfl_xor_sync(0xffffffffu, v[j], 8);
        }
        if (lane < 8) {
            float o4[4];
#pragma unroll
            for (int j = 0; j < 4; j++) {
                const float gg = bfr(silu_f(bfr(gsum[j])));
                const float sg = bfr(bfr(v[j]) * gg);
                o4[j] = x_fin[j] + sg;
            }
            const int rc = cta / 9, ntc = cta - 9 * rc;
            uint2 pk;
            pk.x = pack_bf16(o4[0], o4[1]);
            pk.y = pack_bf16(o4[2], o4[3]);
            *reinterpret_cast<uint2*>(out + (lane >> 1) * kD + kCols3 * rc + 8 * ntc + (lane & 1) * 4) = pk;
        }
        if (tid == 0) TS(17);
        if (cta == 0 && tid == 0) {
            asm volatile("st.relaxed.gpu.global.u32 [%0], %1;" ::"l"(&g_epoch), "r"(epoch + 1u) : "memory");
        }
    }
}

typedef CUresult (*PFN_encodeTiled)(CUtensorMap*, CUtensorMapDataType, cuuint32_t, void*, const cuuint64_t*,
                                    const cuuint64_t*, const cuuint32_t*, const cuuint32_t*, CUtensorMapInterleave,
                                    CUtensorMapSwizzle, CUtensorMapL2promotion, CUtensorMapFloatOOBfill);

void make_map(PFN_encodeTiled enc, CUtensorMap* map, const void* ptr, uint64_t cols, uint64_t rows, uint32_t box_c,
              uint32_t box_r, CUtensorMapSwizzle swz, CUtensorMapL2promotion promo) {
    cuuint64_t gdim[2] = {cols, rows};
    cuuint64_t gstr[1] = {cols * 2};
    cuuint32_t box[2] = {box_c, box_r};
    cuuint32_t estr[2] = {1, 1};
    enc(map, CU_TENSOR_MAP_DATA_TYPE_BFLOAT16, 2, const_cast<void*>(ptr), gdim, gstr, box, estr,
        CU_TENSOR_MAP_INTERLEAVE_NONE, swz, promo, CU_TENSOR_MAP_FLOAT_OOB_FILL_NONE);
}

}

extern "C" void kernel_launch(void* const* d_in, const int* in_sizes, int n_in, void* d_out, int out_size) {
    (void)in_sizes;
    (void)n_in;
    (void)out_size;
    static PFN_encodeTiled enc = nullptr;
    if (!enc) {
        void* fn = nullptr;
        cudaDriverEntryPointQueryResult st;
        cudaGetDriverEntryPoint("cuTensorMapEncodeTiled", &fn, cudaEnableDefault, &st);
        enc = (PFN_encodeTiled)fn;
        cudaFuncSetAttribute(fused_decode_kernel, cudaFuncAttributeMaxDynamicSharedMemorySize, SMEM_BYTES);
    }
    CUtensorMap kmap, vmap, womap, w2map, wqmap, w1map;
    make_map(enc, &wqmap, d_in[3], kNQ, kD, 32, 144, CU_TENSOR_MAP_SWIZZLE_64B, CU_TENSOR_MAP_L2_PROMOTION_L2_128B);
    make_map(enc, &w1map, d_in[6], kF, kD, 40, 144, CU_TENSOR_MAP_SWIZZLE_NONE, CU_TENSOR_MAP_L2_PROMOTION_L2_128B);
    make_map(enc, &kmap, d_in[1], kDh, (uint64_t)kB * kHkv * kSk, 64, kChunkKeys, CU_TENSOR_MAP_SWIZZLE_128B,
             CU_TENSOR_MAP_L2_PROMOTION_L2_256B);
    make_map(enc, &vmap, d_in[2], kDh, (uint64_t)kB * kHkv * kSk, 64, kChunkKeys, CU_TENSOR_MAP_SWIZZLE_128B,
             CU_TENSOR_MAP_L2_PROMOTION_L2_256B);
    make_map(enc, &womap, d_in[4], kD, kNQ, kCols3, 128, CU_TENSOR_MAP_SWIZZLE_NONE,
             CU_TENSOR_MAP_L2_PROMOTION_L2_128B);
    make_map(enc, &w2map, d_in[7], kD, kF, kCols3, 144, CU_TENSOR_MAP_SWIZZLE_NONE,
             CU_TENSOR_MAP_L2_PROMOTION_L2_128B);
    fused_decode_kernel<<<kCTAs, 288, SMEM_BYTES>>>(kmap, vmap, womap, w2map, wqmap, w1map,
                                                    (const __nv_bfloat16*)d_in[0], (__nv_bfloat16*)d_out);
}
```

```cpp
#include <cuda_runtime.h>
#include <cuda_bf16.h>
#include <cuda.h>
#include <stdint.h>

namespace {

constexpr int kB = 4, kD = 576, kHkv = 16, kSk = 4096, kDh = 128, kWin = 1024, kF = 4608;
constexpr int kNQ = 4096;
constexpr int kGroups = 16, kCTAs = 128;
constexpr int kQCols = 256, kHCols = 288;
constexpr int kCols3 = 72;
constexpr int kChunkKeys = 64;
constexpr int kFinalCons = 72;
constexpr int kWindow = 4;
constexpr int kSpinLimit = 1 << 22;

constexpr int kSlotBytes = 16384;
constexpr int OFF_KV = 0;
constexpr int STR_W3 = 144;
constexpr int BOX_WQ = 144 * 64;
constexpr int BOX_W1 = 144 * 80;
constexpr int OFF_A = 8 * kSlotBytes;
constexpr int SZ_A = 4 * BOX_WQ;
constexpr int OFF_B = OFF_A + SZ_A;
constexpr int SZ_B = 4 * BOX_W1;
constexpr int OFF_XN = OFF_B + SZ_B;
constexpr int OFF_Q = OFF_XN + 4 * 584 * 2;
constexpr int OFF_H = OFF_Q + 544;
constexpr int OFF_O = OFF_H + 4 * 296 * 2;
constexpr int OFF_P = OFF_O + 4 * 264 * 2;
constexpr int OFF_ML = OFF_P + 2 * 520 * 2;
constexpr int OFF_STG = OFF_ML + 128;
constexpr int OFF_BAR = OFF_STG + 1024;
constexpr int SMEM_USED = OFF_BAR + 288;
constexpr int SMEM_BYTES = SMEM_USED + 1024;

static_assert(OFF_A % 1024 == 0 && OFF_B % 128 == 0, "align");
static_assert(OFF_BAR % 8 == 0 && OFF_STG % 16 == 0, "align");
static_assert(SMEM_BYTES <= 232448, "smem");

__device__ __align__(128) uint32_t g_qx[kGroups * kB * kQCols];
__device__ __align__(128) uint32_t g_hx[kGroups * kB * kHCols];
__device__ __align__(128) uint32_t g_opart[kGroups * kB * 2 * 272];
__device__ __align__(128) uint32_t g_fpart[kFinalCons * 2 * kGroups * 32];
__device__ uint32_t g_epoch;

__host__ __device__ constexpr int order_at(int n) { return n < 12 ? n : (n < 14 ? n + 8 : (n < 22 ? n - 2 : n)); }

__device__ __forceinline__ uint32_t smem_u32(const void* p) {
    return (uint32_t)__cvta_generic_to_shared(p);
}
__device__ __forceinline__ void mbar_init(uint32_t bar, uint32_t count) {
    asm volatile("mbarrier.init.shared::cta.b64 [%0], %1;" ::"r"(bar), "r"(count) : "memory");
}
__device__ __forceinline__ void mbar_init_fence() {
    asm volatile("fence.mbarrier_init.release.cluster;" ::: "memory");
    asm volatile("fence.proxy.async.shared::cta;" ::: "memory");
}
__device__ __forceinline__ void mbar_expect_tx(uint32_t bar, uint32_t bytes) {
    asm volatile("mbarrier.arrive.expect_tx.shared::cta.b64 _, [%0], %1;" ::"r"(bar), "r"(bytes) : "memory");
}
__device__ __forceinline__ void mbar_arrive(uint32_t bar) {
    asm volatile("mbarrier.arrive.shared::cta.b64 _, [%0];" ::"r"(bar) : "memory");
}
__device__ __forceinline__ bool mbar_try_wait(uint32_t bar, uint32_t parity) {
    uint32_t ok;
    asm volatile(
        "{\n .reg .pred p;\n mbarrier.try_wait.parity.shared::cta.b64 p, [%1], %2;\n selp.u32 %0, 1, 0, p;\n}"
        : "=r"(ok)
        : "r"(bar), "r"(parity)
        : "memory");
    return ok != 0;
}
__device__ __forceinline__ void mbar_wait(uint32_t bar) {
    for (int i = 0; i < kSpinLimit; i++) {
        if (mbar_try_wait(bar, 0)) break;
    }
}
__device__ __forceinline__ void tma_2d_ef(uint32_t dst, const CUtensorMap* map, int c0, int c1, uint32_t bar) {
    uint64_t pol;
    asm volatile("createpolicy.fractional.L2::evict_first.b64 %0, 1.0;" : "=l"(pol));
    asm volatile(
        "cp.async.bulk.tensor.2d.shared::cluster.global.mbarrier::complete_tx::bytes.L2::cache_hint [%0], [%1, {%3, %4}], [%2], %5;" ::"r"(dst),
        "l"(map), "r"(bar), "r"(c0), "r"(c1), "l"(pol)
        : "memory");
}
__device__ __forceinline__ void tma_2d(uint32_t dst, const CUtensorMap* map, int c0, int c1, uint32_t bar) {
    asm volatile(
        "cp.async.bulk.tensor.2d.shared::cluster.global.mbarrier::complete_tx::bytes [%0], [%1, {%3, %4}], [%2];" ::"r"(dst),
        "l"(map), "r"(bar), "r"(c0), "r"(c1)
        : "memory");
}
__device__ __forceinline__ void ldsm_x4(uint32_t addr, uint32_t& r0, uint32_t& r1, uint32_t& r2, uint32_t& r3) {
    asm volatile("ldmatrix.sync.aligned.m8n8.x4.shared.b16 {%0,%1,%2,%3}, [%4];"
                 : "=r"(r0), "=r"(r1), "=r"(r2), "=r"(r3)
                 : "r"(addr)
                 : "memory");
}
__device__ __forceinline__ void ldsm_x4_t(uint32_t addr, uint32_t& r0, uint32_t& r1, uint32_t& r2, uint32_t& r3) {
    asm volatile("ldmatrix.sync.aligned.m8n8.x4.trans.shared.b16 {%0,%1,%2,%3}, [%4];"
                 : "=r"(r0), "=r"(r1), "=r"(r2), "=r"(r3)
                 : "r"(addr)
                 : "memory");
}
__device__ __forceinline__ void ldsm_x2_t(uint32_t addr, uint32_t& r0, uint32_t& r1) {
    asm volatile("ldmatrix.sync.aligned.m8n8.x2.trans.shared.b16 {%0,%1}, [%2];"
                 : "=r"(r0), "=r"(r1)
                 : "r"(addr)
                 : "memory");
}
__device__ __forceinline__ void mma16816(float (&c)[4], uint32_t a0, uint32_t a1, uint32_t a2, uint32_t a3,
                                         uint32_t b0, uint32_t b1) {
    asm volatile(
        "mma.sync.aligned.m16n8k16.row.col.f32.bf16.bf16.f32 {%0,%1,%2,%3}, {%4,%5,%6,%7}, {%8,%9}, {%0,%1,%2,%3};"
        : "+f"(c[0]), "+f"(c[1]), "+f"(c[2]), "+f"(c[3])
        : "r"(a0), "r"(a1), "r"(a2), "r"(a3), "r"(b0), "r"(b1));
}
__device__ __forceinline__ void bar_cons() { asm volatile("bar.sync 1, 256;" ::: "memory"); }

__device__ __forceinline__ float bfr(float x) { return __bfloat162float(__float2bfloat16_rn(x)); }
__device__ __forceinline__ uint32_t pack_bf16(float lo, float hi) {
    __nv_bfloat162 v = __floats2bfloat162_rn(lo, hi);
    return *reinterpret_cast<uint32_t*>(&v);
}
__device__ __forceinline__ uint32_t tagw(float v, uint32_t flag) { return (__float_as_uint(v) & ~1u) | flag; }
__device__ __forceinline__ void st_word2(uint32_t* p, uint32_t v0, uint32_t v1) {
    asm volatile("st.relaxed.gpu.global.v2.u32 [%0], {%1,%2};" ::"l"(p), "r"(v0), "r"(v1) : "memory");
}
__device__ __forceinline__ void st_word4(uint32_t* p, uint32_t a, uint32_t b, uint32_t c, uint32_t d) {
    asm volatile("st.relaxed.gpu.global.v4.u32 [%0], {%1,%2,%3,%4};" ::"l"(p), "r"(a), "r"(b), "r"(c), "r"(d) : "memory");
}
__device__ __forceinline__ uint4 ld_word4(const uint32_t* p) {
    uint4 v;
    asm volatile("ld.relaxed.gpu.global.v4.u32 {%0,%1,%2,%3}, [%4];"
                 : "=r"(v.x), "=r"(v.y), "=r"(v.z), "=r"(v.w)
                 : "l"(p)
                 : "memory");
    return v;
}
__device__ __forceinline__ uint32_t bad4(const uint4& w, uint32_t flag) {
    return (w.x ^ flag) | (w.y ^ flag) | (w.z ^ flag) | (w.w ^ flag);
}
__device__ __forceinline__ float silu_f(float x) { return x / (1.0f + __expf(-x)); }

template <int KSTEPS, int ASTRIDE>
__device__ __forceinline__ void gemv3_tile(uint32_t wbuf, const __nv_bfloat16* act, int nt, int lane, float (&c)[2]) {
    const int gid = lane >> 2, tig = lane & 3, lm_i = lane & 7, lm_j = lane >> 3;
    const uint32_t wb = wbuf + (8 * lm_j + lm_i) * STR_W3 + nt * 16;
    const __nv_bfloat16* ap = act + (gid & 3) * ASTRIDE + 2 * tig;
    float acc[4][4];
#pragma unroll
    for (int i = 0; i < 4; i++) acc[i][0] = acc[i][1] = acc[i][2] = acc[i][3] = 0.f;
#pragma unroll
    for (int kk = 0; kk < KSTEPS / 2; kk++) {
        uint32_t b0, b1, b2, b3;
        ldsm_x4_t(wb + kk * 32 * STR_W3, b0, b1, b2, b3);
        uint32_t a0 = *reinterpret_cast<const uint32_t*>(ap + 32 * kk);
        uint32_t a2 = *reinterpret_cast<const uint32_t*>(ap + 32 * kk + 8);
        uint32_t a4 = *reinterpret_cast<const uint32_t*>(ap + 32 * kk + 16);
        uint32_t a6 = *reinterpret_cast<const uint32_t*>(ap + 32 * kk + 24);
        if (gid >= 4) a0 = a2 = a4 = a6 = 0u;
        mma16816(acc[(2 * kk) & 3], a0, 0u, a2, 0u, b0, b1);
        mma16816(acc[(2 * kk + 1) & 3], a4, 0u, a6, 0u, b2, b3);
    }
    c[0] = (acc[0][0] + acc[1][0]) + (acc[2][0] + acc[3][0]);
    c[1] = (acc[0][1] + acc[1][1]) + (acc[2][1] + acc[3][1]);
}

__global__ void __launch_bounds__(288, 1)
fused_decode_kernel(const __grid_constant__ CUtensorMap kmap, const __grid_constant__ CUtensorMap vmap,
                    const __grid_constant__ CUtensorMap womap, const __grid_constant__ CUtensorMap w2map,
                    const __grid_constant__ CUtensorMap wqmap, const __grid_constant__ CUtensorMap w1map,
                    const __nv_bfloat16* __restrict__ x, __nv_bfloat16* __restrict__ out) {
    extern __shared__ uint8_t smem_raw[];
    const uint32_t raw_u32 = smem_u32(smem_raw);
    const uint32_t sbase = (raw_u32 + 1023u) & ~1023u;
    uint8_t* sgen = smem_raw + (sbase - raw_u32);

    const int tid = threadIdx.x, warp = tid >> 5, lane = tid & 31;
    const int cta = blockIdx.x;
    const int g = cta >> 3, r = cta & 7;
    const int b = r >> 1, half = r & 1;

    const uint32_t bar_full = sbase + OFF_BAR;
    const uint32_t bar_empty = sbase + OFF_BAR + 24 * 8;
    const uint32_t bar_s1 = sbase + OFF_BAR + 32 * 8;
    volatile uint32_t* flag_s = reinterpret_cast<volatile uint32_t*>(sgen + OFF_BAR + 280);

    const int kv_row0 = (b * kHkv + g) * kSk + (kSk - kWin) + half * 512;
    const int hst = (36 * r) >> 3;
    const int hcnt = ((36 * (r + 1)) >> 3) - hst;

    if (warp == 8) {
        if (lane == 0) {
            for (int i = 0; i < 4; i++) mbar_init(bar_full + 8 * i, 1);
            mbar_init_fence();
        }
        __syncwarp();
#pragma unroll
        for (int n = 0; n < 24; n++) {
            const int u = order_at(n);
            if (n == 3) {
                if (lane == 0) {
                    for (int i = 4; i < 32; i++) mbar_init(bar_full + 8 * i, 1);
                    mbar_init(bar_s1, 8);
                    mbar_init_fence();
                }
                __syncwarp();
                asm volatile("bar.arrive 2, 288;" ::: "memory");
            }
            if (n >= kWindow) mbar_wait(bar_full + 8 * order_at(n >= kWindow ? n - kWindow : 0));
            if (n >= 22) mbar_wait(bar_full + 8 * order_at(n - 2));
            const uint32_t bar = bar_full + 8 * u;
            if (u < 2) {
                if (lane == 0) {
                    mbar_expect_tx(bar, 2 * BOX_WQ);
                    tma_2d(sbase + OFF_A + (2 * u) * BOX_WQ, &wqmap, kQCols * g + 32 * r, 144 * (2 * u), bar);
                    tma_2d(sbase + OFF_A + (2 * u + 1) * BOX_WQ, &wqmap, kQCols * g + 32 * r, 144 * (2 * u + 1), bar);
                }
            } else if (u < 4) {
                if (lane == 0) {
                    mbar_expect_tx(bar, 2 * BOX_W1);
                    tma_2d(sbase + OFF_B + (2 * u - 4) * BOX_W1, &w1map, kHCols * g + 8 * hst, 144 * (2 * u - 4), bar);
                    tma_2d(sbase + OFF_B + (2 * u - 3) * BOX_W1, &w1map, kHCols * g + 8 * hst, 144 * (2 * u - 3), bar);
                }
            } else if (u < 20) {
                const int c = (u - 4) & 7;
                if (u >= 12) mbar_wait(bar_empty + 8 * c);
                if (lane == 0) {
                    const CUtensorMap* mp = u >= 12 ? &vmap : &kmap;
                    mbar_expect_tx(bar, kSlotBytes);
                    tma_2d_ef(sbase + OFF_KV + c * kSlotBytes, mp, 0, kv_row0 + kChunkKeys * c, bar);
                    tma_2d_ef(sbase + OFF_KV + c * kSlotBytes + 8192, mp, 64, kv_row0 + kChunkKeys * c, bar);
                }
            } else if (u < 22) {
                mbar_wait(bar_s1);
                if (lane == 0) {
                    mbar_expect_tx(bar, 144 * STR_W3);
                    tma_2d(sbase + OFF_B + (u - 20) * 144 * STR_W3, &w2map, kCols3 * r, kHCols * g + 144 * (u - 20), bar);
                }
            } else {
                mbar_wait(bar_s1);
                if (lane == 0) {
                    mbar_expect_tx(bar, 128 * STR_W3);
                    tma_2d(sbase + OFF_A + (u - 22) * 128 * STR_W3, &womap, kCols3 * r, kQCols * g + 128 * (u - 22), bar);
                }
            }
            __syncwarp();
        }
        asm volatile("bar.sync 3, 288;" ::: "memory");
        mbar_wait(bar_full + 8 * 22);
        mbar_wait(bar_full + 8 * 23);
        const uint32_t flag_p = *flag_s;
        float c[2];
        gemv3_tile<16, 264>(sbase + OFF_A, reinterpret_cast<const __nv_bfloat16*>(sgen + OFF_O), 8, lane, c);
        if (lane < 16)
            st_word2(g_fpart + (size_t)(((r * 9 + 8) * 2 + 0) * kGroups + g) * 32 + 2 * lane, tagw(c[0], flag_p),
                     tagw(c[1], flag_p));
        return;
    }

    uint32_t epoch;
    asm volatile("ld.relaxed.gpu.global.u32 %0, [%1];" : "=r"(epoch) : "l"(&g_epoch) : "memory");
    uint32_t xw[9];
    if (warp < 4) {
        const uint32_t* xr = reinterpret_cast<const uint32_t*>(x + warp * kD);
#pragma unroll
        for (int i = 0; i < 9; i++) xw[i] = __ldg(xr + lane + 32 * i);
    }
    float x_fin[4] = {0.f, 0.f, 0.f, 0.f};
    if (cta < kFinalCons && tid < 8) {
        const int rc = cta / 9, ntc = cta - 9 * rc;
        const uint2 xv = __ldg(reinterpret_cast<const uint2*>(x + (tid >> 1) * kD + kCols3 * rc + 8 * ntc + (tid & 1) * 4));
        x_fin[0] = __uint_as_float(xv.x << 16);
        x_fin[1] = __uint_as_float(xv.x & 0xffff0000u);
        x_fin[2] = __uint_as_float(xv.y << 16);
        x_fin[3] = __uint_as_float(xv.y & 0xffff0000u);
    }
    const uint32_t flag = (epoch + 1u) & 1u;

    __nv_bfloat16* xn_s = reinterpret_cast<__nv_bfloat16*>(sgen + OFF_XN);
    __nv_bfloat16* q_s = reinterpret_cast<__nv_bfloat16*>(sgen + OFF_Q);
    __nv_bfloat16* h_s = reinterpret_cast<__nv_bfloat16*>(sgen + OFF_H);
    __nv_bfloat16* o_s = reinterpret_cast<__nv_bfloat16*>(sgen + OFF_O);
    __nv_bfloat16* p_s = reinterpret_cast<__nv_bfloat16*>(sgen + OFF_P);
    float* ml_s = reinterpret_cast<float*>(sgen + OFF_ML);
    uint32_t* od = g_opart + (size_t)((g * kB + b) * 2 + half) * 272;

    if (tid == 0) *flag_s = flag;
    {
        const uint32_t inv = flag ^ 1u;
        if (tid < 32) {
            st_word4(g_qx + (size_t)(g * kB + (tid >> 3)) * kQCols + 32 * r + 4 * (tid & 7), inv, inv, inv, inv);
        } else if (tid < 32 + 40) {
            const int i = tid - 32, bb = i / 10, c4 = i - bb * 10;
            if (c4 < 2 * hcnt) st_word4(g_hx + (size_t)(g * kB + bb) * kHCols + 8 * hst + 4 * c4, inv, inv, inv, inv);
        } else if (tid >= 96 && tid < 96 + 68) {
            st_word4(od + 4 * (tid - 96), inv, inv, inv, inv);
        } else if (tid >= 184) {
            const int i = tid - 184;
            st_word4(g_fpart + (size_t)(((r * 9 + (i >> 3)) * 2 + 0) * kGroups + g) * 32 + 4 * (i & 7), inv, inv, inv,
                     inv);
        }
    }

    if (warp < 4) {
        float v[18];
        float sum = 0.f;
#pragma unroll
        for (int i = 0; i < 9; i++) {
            v[2 * i] = __uint_as_float(xw[i] << 16);
            v[2 * i + 1] = __uint_as_float(xw[i] & 0xffff0000u);
            sum += v[2 * i] + v[2 * i + 1];
        }
#pragma unroll
        for (int o = 16; o > 0; o >>= 1) sum += __shfl_xor_sync(0xffffffffu, sum, o);
        const float mean = sum * (1.0f / kD);
        float sq = 0.f;
#pragma unroll
        for (int i = 0; i < 18; i++) {
            const float d = v[i] - mean;
            sq += d * d;
        }
#pragma unroll
        for (int o = 16; o > 0; o >>= 1) sq += __shfl_xor_sync(0xffffffffu, sq, o);
        const float m_bf = bfr(mean);
        const float v_bf = bfr(sq * (1.0f / kD));
        const float den = bfr(sqrtf(bfr(v_bf + 1e-5f)));
#pragma unroll
        for (int i = 0; i < 9; i++) {
            const float a0 = bfr(v[2 * i] - m_bf) / den;
            const float a1 = bfr(v[2 * i + 1] - m_bf) / den;
            *reinterpret_cast<uint32_t*>(xn_s + warp * 584 + 2 * (lane + 32 * i)) = pack_bf16(a0, a1);
        }
    }
    asm volatile("bar.sync 2, 288;" ::: "memory");

    const int gid = lane >> 2, tig = lane & 3;
    const int lm_i = lane & 7, lm_j = lane >> 3;

    {
        const __nv_bfloat16* ap = xn_s + (gid & 3) * 584 + 2 * tig;
#pragma unroll 1
        for (int job = 7 - warp; job < 9; job += 8) {
            const bool isq = job < 4;
            const int nt = isq ? job : job - 4;
            if (!isq && nt >= hcnt) break;
            float acc[4][4];
#pragma unroll
            for (int i = 0; i < 4; i++) acc[i][0] = acc[i][1] = acc[i][2] = acc[i][3] = 0.f;
#pragma unroll 1
            for (int bx = 0; bx < 4; bx++) {
                if ((bx & 1) == 0) mbar_wait(bar_full + 8 * ((isq ? 0 : 2) + (bx >> 1)));
#pragma unroll
                for (int kk = 0; kk < 5; kk++) {
                    const int row = 32 * kk + 8 * lm_j + lm_i;
                    uint32_t addr;
                    if (isq)
                        addr = sbase + OFF_A + bx * BOX_WQ + row * 64 + ((nt ^ ((row >> 1) & 3)) << 4);
                    else
                        addr = sbase + OFF_B + bx * BOX_W1 + row * 80 + nt * 16;
                    const int k0 = 144 * bx + 32 * kk;
                    uint32_t a0 = *reinterpret_cast<const uint32_t*>(ap + k0);
                    uint32_t a2 = *reinterpret_cast<const uint32_t*>(ap + k0 + 8);
                    if (gid >= 4) a0 = a2 = 0u;
                    if (kk < 4) {
                        uint32_t b0, b1, b2, b3;
                        ldsm_x4_t(addr, b0, b1, b2, b3);
                        uint32_t a4 = *reinterpret_cast<const uint32_t*>(ap + k0 + 16);
                        uint32_t a6 = *reinterpret_cast<const uint32_t*>(ap + k0 + 24);
                        if (gid >= 4) a4 = a6 = 0u;
                        mma16816(acc[(2 * kk) & 3], a0, 0u, a2, 0u, b0, b1);
                        mma16816(acc[(2 * kk + 1) & 3], a4, 0u, a6, 0u, b2, b3);
                    } else {
                        uint32_t b0, b1;
                        ldsm_x2_t(addr, b0, b1);
                        mma16816(acc[0], a0, 0u, a2, 0u, b0, b1);
                    }
                }
            }
            const float c0 = (acc[0][0] + acc[1][0]) + (acc[2][0] + acc[3][0]);
            const float c1 = (acc[0][1] + acc[1][1]) + (acc[2][1] + acc[3][1]);
            if (gid < 4) {
                if (isq) {
                    const uint32_t pk = pack_bf16(c0, c1);
                    st_word2(g_qx + (size_t)(g * kB + gid) * kQCols + 32 * r + 8 * nt + 2 * tig, (pk << 16) | flag,
                             (pk & 0xffff0000u) | flag);
                } else {
                    const uint32_t pk = pack_bf16(silu_f(bfr(c0)), silu_f(bfr(c1)));
                    st_word2(g_hx + (size_t)(g * kB + gid) * kHCols + 8 * (hst + nt) + 2 * tig, (pk << 16) | flag,
                             (pk & 0xffff0000u) | flag);
                }
            }
        }
    }
    __syncwarp();
    if (lane == 0) mbar_arrive(bar_s1);

    if (warp == 4 || warp == 5) {
        const int t = tid - 128;
        const uint32_t* src = g_qx + (size_t)(g * kB + b) * kQCols + 4 * t;
        uint4 w;
        for (int it = 0; it < kSpinLimit; it++) {
            w = ld_word4(src);
            if (!(bad4(w, flag) & 1u)) break;
        }
        uint2 pk;
        pk.x = (w.x >> 16) | (w.y & 0xffff0000u);
        pk.y = (w.z >> 16) | (w.w & 0xffff0000u);
        *reinterpret_cast<uint2*>(q_s + (t >> 5) * 136 + 4 * (t & 31)) = pk;
    }
    bar_cons();

    float sc[8][2];
    {
        const uint32_t slot = sbase + OFF_KV + warp * kSlotBytes;
        uint32_t qa[16];
#pragma unroll
        for (int j = 0; j < 8; j++) {
            qa[2 * j] = gid < 2 ? *reinterpret_cast<const uint32_t*>(q_s + gid * 136 + 16 * j + 2 * tig) : 0u;
            qa[2 * j + 1] = gid < 2 ? *reinterpret_cast<const uint32_t*>(q_s + gid * 136 + 16 * j + 8 + 2 * tig) : 0u;
        }
        mbar_wait(bar_full + 8 * (4 + warp));
        float mx = -INFINITY;
        const float scale = 0.08838834764831845f;
#pragma unroll
        for (int nt = 0; nt < 8; nt++) {
            float acc[4] = {0.f, 0.f, 0.f, 0.f};
#pragma unroll
            for (int kk = 0; kk < 4; kk++) {
                const int cg = 4 * kk + lm_j;
                const uint32_t addr =
                    slot + (cg >> 3) * 8192 + (8 * nt + lm_i) * 128 + (((cg & 7) ^ lm_i) << 4);
                uint32_t b0, b1, b2, b3;
                ldsm_x4(addr, b0, b1, b2, b3);
                mma16816(acc, qa[4 * kk], 0u, qa[4 * kk + 1], 0u, b0, b1);
                mma16816(acc, qa[4 * kk + 2], 0u, qa[4 * kk + 3], 0u, b2, b3);
            }
            sc[nt][0] = bfr(bfr(acc[0]) * scale);
            sc[nt][1] = bfr(bfr(acc[1]) * scale);
            mx = fmaxf(mx, fmaxf(sc[nt][0], sc[nt][1]));
        }
        __syncwarp();
        if (lane == 0) mbar_arrive(bar_empty + 8 * warp);
        mx = fmaxf(mx, __shfl_xor_sync(0xffffffffu, mx, 1));
        mx = fmaxf(mx, __shfl_xor_sync(0xffffffffu, mx, 2));
        if (lane == 0 || lane == 4) ml_s[(lane >> 2) * 8 + warp] = mx;
    }

    for (int idx = tid; idx < kB * kHCols / 4; idx += 256) {
        const uint32_t* src = g_hx + (size_t)g * kB * kHCols + 4 * idx;
        uint4 w;
        for (int it = 0; it < kSpinLimit; it++) {
            w = ld_word4(src);
            if (!(bad4(w, flag) & 1u)) break;
        }
        const int bb = idx / 72, c4 = idx - bb * 72;
        uint2 pk;
        pk.x = (w.x >> 16) | (w.y & 0xffff0000u);
        pk.y = (w.z >> 16) | (w.w & 0xffff0000u);
        *reinterpret_cast<uint2*>(h_s + bb * 296 + 4 * c4) = pk;
    }
    bar_cons();

    {
        const int hh = gid & 1;
        float M = ml_s[hh * 8];
#pragma unroll
        for (int w = 1; w < 8; w++) M = fmaxf(M, ml_s[hh * 8 + w]);
        const float l2e = 1.4426950408889634f;
        float lsum = 0.f;
#pragma unroll
        for (int nt = 0; nt < 8; nt++) {
            const float p0 = exp2f((sc[nt][0] - M) * l2e);
            const float p1 = exp2f((sc[nt][1] - M) * l2e);
            lsum += p0 + p1;
            if (gid < 2) *reinterpret_cast<uint32_t*>(p_s + gid * 520 + 64 * warp + 8 * nt + 2 * tig) = pack_bf16(p0, p1);
        }
        lsum += __shfl_xor_sync(0xffffffffu, lsum, 1);
        lsum += __shfl_xor_sync(0xffffffffu, lsum, 2);
        if (lane == 0 || lane == 4) ml_s[16 + (lane >> 2) * 8 + warp] = lsum;
    }
    bar_cons();
    if (tid == 64) {
        float M0 = ml_s[0], L0 = ml_s[16], M1 = ml_s[8], L1 = ml_s[24];
#pragma unroll
        for (int w = 1; w < 8; w++) {
            M0 = fmaxf(M0, ml_s[w]);
            L0 += ml_s[16 + w];
            M1 = fmaxf(M1, ml_s[8 + w]);
            L1 += ml_s[24 + w];
        }
        st_word4(od + 256, tagw(M0, flag), tagw(L0, flag), tagw(M1, flag), tagw(L1, flag));
    }

    {
        float oc[2][4] = {{0.f, 0.f, 0.f, 0.f}, {0.f, 0.f, 0.f, 0.f}};
        const int cg = 2 * warp + (lm_j & 1);
        const uint32_t vbase =
            sbase + OFF_KV + (cg >> 3) * 8192 + ((lm_j >> 1) * 8 + lm_i) * 128 + (((cg & 7) ^ lm_i) << 4);
        const __nv_bfloat16* pp = p_s + (gid & 1) * 520 + 2 * tig;
#pragma unroll 1
        for (int c = 0; c < 8; c++) {
            uint32_t pb[8];
#pragma unroll
            for (int j = 0; j < 8; j++) {
                pb[j] = *reinterpret_cast<const uint32_t*>(pp + 64 * c + 8 * j);
                if (gid >= 2) pb[j] = 0u;
            }
            if (c == 3) {
                mbar_wait(bar_full + 8 * 20);
                mbar_wait(bar_full + 8 * 21);
                for (int nt = 7 - warp; nt < 9; nt += 8) {
                    float cc[2];
                    gemv3_tile<18, 296>(sbase + OFF_B, h_s, nt, lane, cc);
                    if (lane < 16)
                        st_word2(g_fpart + (size_t)(((r * 9 + nt) * 2 + 1) * kGroups + g) * 32 + 2 * lane,
                                 tagw(cc[0], flag), tagw(cc[1], flag));
                }
            }
            mbar_wait(bar_full + 8 * (12 + c));
#pragma unroll
            for (int ks = 0; ks < 4; ks++) {
                uint32_t a0, a1, a2, a3;
                ldsm_x4_t(vbase + c * kSlotBytes + ks * 16 * 128, a0, a1, a2, a3);
                mma16816(oc[ks & 1], a0, a1, a2, a3, pb[2 * ks], pb[2 * ks + 1]);
            }
        }
        float* stg = reinterpret_cast<float*>(sgen + OFF_STG) + warp * 32;
        if (tig == 0) {
            stg[gid] = oc[0][0] + oc[1][0];
            stg[16 + gid] = oc[0][1] + oc[1][1];
            stg[gid + 8] = oc[0][2] + oc[1][2];
            stg[16 + gid + 8] = oc[0][3] + oc[1][3];
        }
        __syncwarp();
        if (lane < 8) {
            const float4 v = *reinterpret_cast<const float4*>(stg + 4 * lane);
            st_word4(od + (lane >> 2) * 128 + 16 * warp + 4 * (lane & 3), tagw(v.x, flag), tagw(v.y, flag),
                     tagw(v.z, flag), tagw(v.w, flag));
        }
    }

    {
        const int bb = tid >> 6, head = (tid >> 5) & 1, d4 = tid & 31;
        const uint32_t* src = g_opart + (size_t)((g * kB + bb) * 2) * 272;
        uint4 wa, wb, sa, sb;
        for (int it = 0; it < kSpinLimit; it++) {
            wa = ld_word4(src + head * 128 + 4 * d4);
            wb = ld_word4(src + 272 + head * 128 + 4 * d4);
            sa = ld_word4(src + 256);
            sb = ld_word4(src + 272 + 256);
            if (!((bad4(wa, flag) | bad4(wb, flag) | bad4(sa, flag) | bad4(sb, flag)) & 1u)) break;
        }
        const float m0 = __uint_as_float(head ? sa.z : sa.x), l0 = __uint_as_float(head ? sa.w : sa.y);
        const float m1 = __uint_as_float(head ? sb.z : sb.x), l1 = __uint_as_float(head ? sb.w : sb.y);
        const float MM = fmaxf(m0, m1);
        const float e0 = exp2f((m0 - MM) * 1.4426950408889634f), e1 = exp2f((m1 - MM) * 1.4426950408889634f);
        const float inv = 1.0f / (e0 * l0 + e1 * l1);
        const float f0 = e0 * inv, f1 = e1 * inv;
        uint2 pk;
        pk.x = pack_bf16(f0 * __uint_as_float(wa.x) + f1 * __uint_as_float(wb.x),
                         f0 * __uint_as_float(wa.y) + f1 * __uint_as_float(wb.y));
        pk.y = pack_bf16(f0 * __uint_as_float(wa.z) + f1 * __uint_as_float(wb.z),
                         f0 * __uint_as_float(wa.w) + f1 * __uint_as_float(wb.w));
        *reinterpret_cast<uint2*>(o_s + bb * 264 + head * 128 + 4 * d4) = pk;
    }
    asm volatile("bar.sync 3, 288;" ::: "memory");

    {
        mbar_wait(bar_full + 8 * 22);
        mbar_wait(bar_full + 8 * 23);
        float c[2];
        gemv3_tile<16, 264>(sbase + OFF_A, o_s, warp, lane, c);
        if (lane < 16)
            st_word2(g_fpart + (size_t)(((r * 9 + warp) * 2 + 0) * kGroups + g) * 32 + 2 * lane, tagw(c[0], flag),
                     tagw(c[1], flag));
    }

    if (cta < kFinalCons && warp == 0) {
        const int gh = lane >> 4, which = (lane >> 3) & 1, bc = lane & 7;
        const uint32_t* src = g_fpart + (size_t)cta * 1024 + (which * kGroups + gh * 8) * 32 + bc * 4;
        uint4 w[8];
        for (int it = 0; it < kSpinLimit; it++) {
            uint32_t bad = 0;
#pragma unroll
            for (int i = 0; i < 8; i++) {
                w[i] = ld_word4(src + i * 32);
                bad |= bad4(w[i], flag);
            }
            if (!__any_sync(0xffffffffu, bad & 1u)) break;
        }
        float v[4] = {0.f, 0.f, 0.f, 0.f};
#pragma unroll
        for (int i = 0; i < 8; i++) {
            v[0] += __uint_as_float(w[i].x);
            v[1] += __uint_as_float(w[i].y);
            v[2] += __uint_as_float(w[i].z);
            v[3] += __uint_as_float(w[i].w);
        }
        float gsum[4];
#pragma unroll
        for (int j = 0; j < 4; j++) {
            v[j] += __shfl_xor_sync(0xffffffffu, v[j], 16);
            gsum[j] = __shfl_xor_sync(0xffffffffu, v[j], 8);
        }
        if (lane < 8) {
            float o4[4];
#pragma unroll
            for (int j = 0; j < 4; j++) {
                const float gg = bfr(silu_f(bfr(gsum[j])));
                const float sg = bfr(bfr(v[j]) * gg);
                o4[j] = x_fin[j] + sg;
            }
            const int rc = cta / 9, ntc = cta - 9 * rc;
            uint2 pk;
            pk.x = pack_bf16(o4[0], o4[1]);
            pk.y = pack_bf16(o4[2], o4[3]);
            *reinterpret_cast<uint2*>(out + (lane >> 1) * kD + kCols3 * rc + 8 * ntc + (lane & 1) * 4) = pk;
        }
        if (cta == 0 && tid == 0) {
            asm volatile("st.relaxed.gpu.global.u32 [%0], %1;" ::"l"(&g_epoch), "r"(epoch + 1u) : "memory");
        }
    }
}

typedef CUresult (*PFN_encodeTiled)(CUtensorMap*, CUtensorMapDataType, cuuint32_t, void*, const cuuint64_t*,
                                    const cuuint64_t*, const cuuint32_t*, const cuuint32_t*, CUtensorMapInterleave,
                                    CUtensorMapSwizzle, CUtensorMapL2promotion, CUtensorMapFloatOOBfill);

void make_map(PFN_encodeTiled enc, CUtensorMap* map, const void* ptr, uint64_t cols, uint64_t rows, uint32_t box_c,
              uint32_t box_r, CUtensorMapSwizzle swz, CUtensorMapL2promotion promo) {
    cuuint64_t gdim[2] = {cols, rows};
    cuuint64_t gstr[1] = {cols * 2};
    cuuint32_t box[2] = {box_c, box_r};
    cuuint32_t estr[2] = {1, 1};
    enc(map, CU_TENSOR_MAP_DATA_TYPE_BFLOAT16, 2, const_cast<void*>(ptr), gdim, gstr, box, estr,
        CU_TENSOR_MAP_INTERLEAVE_NONE, swz, promo, CU_TENSOR_MAP_FLOAT_OOB_FILL_NONE);
}

}

extern "C" void kernel_launch(void* const* d_in, const int* in_sizes, int n_in, void* d_out, int out_size) {
    (void)in_sizes;
    (void)n_in;
    (void)out_size;
    static PFN_encodeTiled enc = nullptr;
    if (!enc) {
        void* fn = nullptr;
        cudaDriverEntryPointQueryResult st;
        cudaGetDriverEntryPoint("cuTensorMapEncodeTiled", &fn, cudaEnableDefault, &st);
        enc = (PFN_encodeTiled)fn;
        cudaFuncSetAttribute(fused_decode_kernel, cudaFuncAttributeMaxDynamicSharedMemorySize, SMEM_BYTES);
    }
    CUtensorMap kmap, vmap, womap, w2map, wqmap, w1map;
    make_map(enc, &wqmap, d_in[3], kNQ, kD, 32, 144, CU_TENSOR_MAP_SWIZZLE_64B, CU_TENSOR_MAP_L2_PROMOTION_L2_128B);
    make_map(enc, &w1map, d_in[6], kF, kD, 40, 144, CU_TENSOR_MAP_SWIZZLE_NONE, CU_TENSOR_MAP_L2_PROMOTION_L2_128B);
    make_map(enc, &kmap, d_in[1], kDh, (uint64_t)kB * kHkv * kSk, 64, kChunkKeys, CU_TENSOR_MAP_SWIZZLE_128B,
             CU_TENSOR_MAP_L2_PROMOTION_L2_256B);
    make_map(enc, &vmap, d_in[2], kDh, (uint64_t)kB * kHkv * kSk, 64, kChunkKeys, CU_TENSOR_MAP_SWIZZLE_128B,
             CU_TENSOR_MAP_L2_PROMOTION_L2_256B);
    make_map(enc, &womap, d_in[4], kD, kNQ, kCols3, 128, CU_TENSOR_MAP_SWIZZLE_NONE,
             CU_TENSOR_MAP_L2_PROMOTION_L2_128B);
    make_map(enc, &w2map, d_in[7], kD, kF, kCols3, 144, CU_TENSOR_MAP_SWIZZLE_NONE,
             CU_TENSOR_MAP_L2_PROMOTION_L2_128B);
    fused_decode_kernel<<<kCTAs, 288, SMEM_BYTES>>>(kmap, vmap, womap, w2map, wqmap, w1map,
                                                    (const __nv_bfloat16*)d_in[0], (__nv_bfloat16*)d_out);
}
```
